```python
import torch

def _softmax(x, axis=-1):
    return torch.softmax(x, dim=axis)
def _gelu(x):
    return torch.nn.functional.gelu(x, approximate="tanh")
def _silu(x):
    return torch.nn.functional.silu(x)
def _sigmoid(x):
    return torch.sigmoid(x)
def _layernorm(x, axis=-1, eps=1e-5):
    m = x.mean(dim=axis, keepdim=True)
    v = x.var(dim=axis, keepdim=True, unbiased=False)
    return (x - m) / torch.sqrt(v + eps)
def _scatter_add(tgt, idx, src, axis=0):
    return tgt.clone().index_add_(axis, idx, src)
def _segment_sum(src, seg, n):
    out = torch.zeros((n,) + src.shape[1:], dtype=src.dtype)
    return out.index_add_(0, seg, src)
def _pad(x, pw):
    flat = tuple(v for pair in reversed(pw) for v in pair)
    return torch.nn.functional.pad(x, flat)

kernel_name = 'recurrent_scan__spectral_gfnet__glu_gated_glu__prompt'

def setup_inputs():

    _w = (lambda a: (lambda t: t.to(torch.bfloat16) if t.is_floating_point() else t)(torch.as_tensor(a)))
    def _A_setup():
        B, S, D = 1, 2048, 640
        Df = D // 2 + 1
        return {
            "x": _w((lambda *s: torch.randn(*s, dtype=torch.bfloat16) * 0.05)(B, S, D)),
            "w_r": _w((lambda *s: torch.randn(*s, dtype=torch.bfloat16) * 0.05)(S, Df) * 0.02),
            "w_i": _w((lambda *s: torch.randn(*s, dtype=torch.bfloat16) * 0.05)(S, Df) * 0.02),
        }
    _A_in = _A_setup()

    def _B_setup():
        B, S, D, F = 1, 2048, 640, 1728
        return {
            "x": _w((lambda *s: torch.randn(*s, dtype=torch.bfloat16) * 0.05)(B, S, D)),
            "w_gate": _w((lambda *s: torch.randn(*s, dtype=torch.bfloat16) * 1.6)(D, F)),
            "w_up": _w((lambda *s: torch.randn(*s, dtype=torch.bfloat16) * 0.1)(D, F)),
            "w_down": _w((lambda *s: torch.randn(*s, dtype=torch.bfloat16) * 0.1)(F, D)),
        }
    _B_in = _B_setup()

    return {
        "A_x": _A_in["x"],
        "A_w_r": _A_in["w_r"],
        "A_w_i": _A_in["w_i"],
        "B_x": _B_in["x"],
        "B_w_gate": _B_in["w_gate"],
        "B_w_up": _B_in["w_up"],
        "B_w_down": _B_in["w_down"],
    }

def reference(A_x, A_w_r, A_w_i, B_x, B_w_gate, B_w_up, B_w_down):
    def _A_ref(x, w_r, w_i):
        B, S, D = x.shape
        X = (lambda x, axes=(-2,-1): torch.fft.rfft2(x.float(), dim=axes))(x, axes=(-2, -1))
        W = w_r + 1j * w_i
        X = X * W
        y = (lambda x, s, axes=(-2,-1): torch.fft.irfft2(x, s=s, dim=axes).to(torch.bfloat16))(X, (S, D), axes=(-2, -1))
        return y

    def _B_ref(x, w_gate, w_up, w_down):
        g = torch.einsum("bsd,df->bsf", x, w_gate)
        u = torch.einsum("bsd,df->bsf", x, w_up)
        h = _sigmoid(g) * u
        return torch.einsum("bsf,fd->bsd", h, w_down)

    x = A_x
    xn = _layernorm(x, axis=-1)
    s = _A_ref(xn, A_w_r, A_w_i)
    g = _silu(_B_ref(xn, B_w_gate, B_w_up, B_w_down))
    return x + s * g
```

```cpp
#include <cuda_runtime.h>
#include <cuda_bf16.h>
#include <cuda_fp16.h>
#include <cuda.h>
#include <stdint.h>

#define R_CHORE 32
#define R_AUX 112
#define R_CONS 184
#define POLL_NS 40
#define FILL_NS 0
#define WS_NS 1500
#define CONV_CONS 0
#define PIECE 4096
#define PIECE2 4096
#define ST_NS 0
#define LD_NS 300
#define PF_NS 300

namespace {

__device__ const __align__(128) uint32_t g_tab[9728] = {
0x290f290f,0x290f290f,0x290f290f,0x290f290f,0x290f290f,0x290f290f,0x290f290f,0x290f290f,0x290f290f,0x290f290f,0x290f290f,0x290f290f,
0x290f290f,0x290f290f,0x290f290f,0x290f290f,0x290f290f,0x290f290f,0x290f290f,0x290f290f,0x290f290f,0x290f290f,0x290f290f,0x290f290f,
0x290f290f,0x290f290f,0x290f290f,0x290f290f,0x290f290f,0x290f290f,0x290f290f,0x290f290f,0x266b2728,0x24c5259f,0x21e023bf,0x1bef1fe6,
0x2909290f,0x28d728f6,0x287628ad,0x27d32835,0xa7d3a728,0xa876a835,0xa8d7a8ad,0xa909a8f6,0x9bef0000,0xa1e09fe6,0xa4c5a3bf,0xa66ba59f,
0xa66ba728,0xa4c5a59f,0xa1e0a3bf,0x9bef9fe6,0xa909a90f,0xa8d7a8f6,0xa876a8ad,0xa7d3a835,0x27d32728,0x28762835,0x28d728ad,0x290928f6,
0x1bef8000,0x21e01fe6,0x24c523bf,0x266b259f,0xa8f6a90f,0xa835a8ad,0xa59fa728,0x9fe6a3bf,0x1fe68000,0x259f23bf,0x28352728,0x28f628ad,
0x28f6290f,0x283528ad,0x259f2728,0x1fe623bf,0x9fe60000,0xa59fa3bf,0xa835a728,0xa8f6a8ad,0xa8f6a90f,0xa835a8ad,0xa59fa728,0x9fe6a3bf,
0x1fe68000,0x259f23bf,0x28352728,0x28f628ad,0x28f6290f,0x283528ad,0x259f2728,0x1fe623bf,0x9fe60000,0xa59fa3bf,0xa835a728,0xa8f6a8ad,
0x24c52728,0x9bef1fe6,0xa66ba3bf,0xa8d7a835,0x21e08000,0x27d3259f,0x290928ad,0x287628f6,0xa876a728,0xa909a8f6,0xa7d3a8ad,0xa1e0a59f,
0x28d7290f,0x266b2835,0x1bef23bf,0xa4c59fe6,0xa4c5a728,0x1bef9fe6,0x266b23bf,0x28d72835,0xa1e00000,0xa7d3a59f,0xa909a8ad,0xa876a8f6,
0x28762728,0x290928f6,0x27d328ad,0x21e0259f,0xa8d7a90f,0xa66ba835,0x9befa3bf,0x24c51fe6,0x28ad290f,0x23bf2728,0xa3bf0000,0xa8ada728,
0xa8ada90f,0xa3bfa728,0x23bf8000,0x28ad2728,0x28ad290f,0x23bf2728,0xa3bf0000,0xa8ada728,0xa8ada90f,0xa3bfa728,0x23bf8000,0x28ad2728,
0x28ad290f,0x23bf2728,0xa3bf0000,0xa8ada728,0xa8ada90f,0xa3bfa728,0x23bf8000,0x28ad2728,0x28ad290f,0x23bf2728,0xa3bf0000,0xa8ada728,
0xa8ada90f,0xa3bfa728,0x23bf8000,0x28ad2728,0x21e02728,0xa66b9fe6,0xa909a8ad,0xa4c5a835,0xa876a90f,0x9befa59f,0x27d323bf,0x28d728f6,
0xa8d7a728,0xa7d3a8f6,0x1befa3bf,0x2876259f,0x24c58000,0x29092835,0x266b28ad,0xa1e01fe6,0xa1e0a728,0x266b1fe6,0x290928ad,0x24c52835,
0x2876290f,0x1bef259f,0xa7d3a3bf,0xa8d7a8f6,0x28d72728,0x27d328f6,0x9bef23bf,0xa876a59f,0xa4c50000,0xa909a835,0xa66ba8ad,0x21e09fe6,
0xa835a90f,0x1fe6a3bf,0x28f62728,0x259f28ad,0xa59f0000,0xa8f6a8ad,0x9fe6a728,0x283523bf,0x2835290f,0x9fe623bf,0xa8f6a728,0xa59fa8ad,
0x259f8000,0x28f628ad,0x1fe62728,0xa835a3bf,0xa835a90f,0x1fe6a3bf,0x28f62728,0x259f28ad,0xa59f0000,0xa8f6a8ad,0x9fe6a728,0x283523bf,
0x2835290f,0x9fe623bf,0xa8f6a728,0xa59fa8ad,0x259f8000,0x28f628ad,0x1fe62728,0xa835a3bf,0x1bef2728,0xa8d7a59f,0xa4c5a8ad,0x27d31fe6,
0xa66b0000,0xa876a8f6,0x21e0a3bf,0x29092835,0xa909a728,0xa1e0a835,0x287623bf,0x266b28f6,0xa7d3a90f,0x24c59fe6,0x28d728ad,0x9bef259f,
0x9befa728,0x28d7259f,0x24c528ad,0xa7d39fe6,0x266b8000,0x287628f6,0xa1e023bf,0xa909a835,0x29092728,0x21e02835,0xa876a3bf,0xa66ba8f6,
0x27d3290f,0xa4c51fe6,0xa8d7a8ad,0x1befa59f,0xa90f290f,0xa90f290f,0xa90f290f,0xa90f290f,0xa90f290f,0xa90f290f,0xa90f290f,0xa90f290f,
0xa90f290f,0xa90f290f,0xa90f290f,0xa90f290f,0xa90f290f,0xa90f290f,0xa90f290f,0xa90f290f,0xa90f290f,0xa90f290f,0xa90f290f,0xa90f290f,
0xa90f290f,0xa90f290f,0xa90f290f,0xa90f290f,0xa90f290f,0xa90f290f,0xa90f290f,0xa90f290f,0xa90f290f,0xa90f290f,0xa90f290f,0xa90f290f,
0xa7d3a728,0xa876a835,0xa8d7a8ad,0xa909a8f6,0x9bef8000,0xa1e09fe6,0xa4c5a3bf,0xa66ba59f,0xa66ba728,0xa4c5a59f,0xa1e0a3bf,0x9bef9fe6,
0xa909a90f,0xa8d7a8f6,0xa876a8ad,0xa7d3a835,0x27d32728,0x28762835,0x28d728ad,0x290928f6,0x1bef8000,0x21e01fe6,0x24c523bf,0x266b259f,
0x266b2728,0x24c5259f,0x21e023bf,0x1bef1fe6,0x2909290f,0x28d728f6,0x287628ad,0x27d32835,0x1fe68000,0x259f23bf,0x28352728,0x28f628ad,
0x28f6290f,0x283528ad,0x259f2728,0x1fe623bf,0x9fe68000,0xa59fa3bf,0xa835a728,0xa8f6a8ad,0xa8f6a90f,0xa835a8ad,0xa59fa728,0x9fe6a3bf,
0x1fe68000,0x259f23bf,0x28352728,0x28f628ad,0x28f6290f,0x283528ad,0x259f2728,0x1fe623bf,0x9fe68000,0xa59fa3bf,0xa835a728,0xa8f6a8ad,
0xa8f6a90f,0xa835a8ad,0xa59fa728,0x9fe6a3bf,0xa876a728,0xa909a8f6,0xa7d3a8ad,0xa1e0a59f,0x28d7290f,0x266b2835,0x1bef23bf,0xa4c59fe6,
0xa4c5a728,0x1bef9fe6,0x266b23bf,0x28d72835,0xa1e08000,0xa7d3a59f,0xa909a8ad,0xa876a8f6,0x28762728,0x290928f6,0x27d328ad,0x21e0259f,
0xa8d7a90f,0xa66ba835,0x9befa3bf,0x24c51fe6,0x24c52728,0x9bef1fe6,0xa66ba3bf,0xa8d7a835,0x21e08000,0x27d3259f,0x290928ad,0x287628f6,
0xa3bf8000,0xa8ada728,0xa8ada90f,0xa3bfa728,0x23bf8000,0x28ad2728,0x28ad290f,0x23bf2728,0xa3bf8000,0xa8ada728,0xa8ada90f,0xa3bfa728,
0x23bf8000,0x28ad2728,0x28ad290f,0x23bf2728,0xa3bf8000,0xa8ada728,0xa8ada90f,0xa3bfa728,0x23bf8000,0x28ad2728,0x28ad290f,0x23bf2728,
0xa3bf8000,0xa8ada728,0xa8ada90f,0xa3bfa728,0x23bf8000,0x28ad2728,0x28ad290f,0x23bf2728,0xa8d7a728,0xa7d3a8f6,0x1befa3bf,0x2876259f,
0x24c58000,0x29092835,0x266b28ad,0xa1e01fe6,0xa1e0a728,0x266b1fe6,0x290928ad,0x24c52835,0x2876290f,0x1bef259f,0xa7d3a3bf,0xa8d7a8f6,
0x28d72728,0x27d328f6,0x9bef23bf,0xa876a59f,0xa4c58000,0xa909a835,0xa66ba8ad,0x21e09fe6,0x21e02728,0xa66b9fe6,0xa909a8ad,0xa4c5a835,
0xa876a90f,0x9befa59f,0x27d323bf,0x28d728f6,0x259f8000,0x28f628ad,0x1fe62728,0xa835a3bf,0xa835a90f,0x1fe6a3bf,0x28f62728,0x259f28ad,
0xa59f8000,0xa8f6a8ad,0x9fe6a728,0x283523bf,0x2835290f,0x9fe623bf,0xa8f6a728,0xa59fa8ad,0x259f8000,0x28f628ad,0x1fe62728,0xa835a3bf,
0xa835a90f,0x1fe6a3bf,0x28f62728,0x259f28ad,0xa59f8000,0xa8f6a8ad,0x9fe6a728,0x283523bf,0x2835290f,0x9fe623bf,0xa8f6a728,0xa59fa8ad,
0xa909a728,0xa1e0a835,0x287623bf,0x266b28f6,0xa7d3a90f,0x24c59fe6,0x28d728ad,0x9bef259f,0x9befa728,0x28d7259f,0x24c528ad,0xa7d39fe6,
0x266b8000,0x287628f6,0xa1e023bf,0xa909a835,0x29092728,0x21e02835,0xa876a3bf,0xa66ba8f6,0x27d3290f,0xa4c51fe6,0xa8d7a8ad,0x1befa59f,
0x1bef2728,0xa8d7a59f,0xa4c5a8ad,0x27d31fe6,0xa66b8000,0xa876a8f6,0x21e0a3bf,0x29092835,0x2728290f,0xa7280000,0xa728a90f,0x27288000,
0x2728290f,0xa7280000,0xa728a90f,0x27288000,0x2728290f,0xa7280000,0xa728a90f,0x27288000,0x2728290f,0xa7280000,0xa728a90f,0x27288000,
0x2728290f,0xa7280000,0xa728a90f,0x27288000,0x2728290f,0xa7280000,0xa728a90f,0x27288000,0x2728290f,0xa7280000,0xa728a90f,0x27288000,
0x2728290f,0xa7280000,0xa728a90f,0x27288000,0x9bef2728,0xa8d7a835,0x24c5a3bf,0x27d328f6,0x266b290f,0xa8769fe6,0xa1e0a8ad,0x2909259f,
0xa909a728,0x21e0a59f,0x287628ad,0xa66b1fe6,0xa7d30000,0xa4c5a8f6,0x28d723bf,0x1bef2835,0x1befa728,0x28d72835,0xa4c523bf,0xa7d3a8f6,
0xa66ba90f,0x28761fe6,0x21e028ad,0xa909a59f,0x29092728,0xa1e0259f,0xa876a8ad,0x266b9fe6,0x27d38000,0x24c528f6,0xa8d7a3bf,0x9befa835,
0xa59fa90f,0x28f623bf,0x9fe62728,0xa835a8ad,0x28358000,0x1fe628ad,0xa8f6a728,0x259fa3bf,0x259f290f,0xa8f6a3bf,0x1fe6a728,0x283528ad,
0xa8350000,0x9fe6a8ad,0x28f62728,0xa59f23bf,0xa59fa90f,0x28f623bf,0x9fe62728,0xa835a8ad,0x28358000,0x1fe628ad,0xa8f6a728,0x259fa3bf,
0x259f290f,0xa8f6a3bf,0x1fe6a728,0x283528ad,0xa8350000,0x9fe6a8ad,0x28f62728,0xa59f23bf,0xa1e02728,0xa66ba8f6,0x290923bf,0xa4c5259f,
0x28768000,0x9bef2835,0xa7d3a8ad,0x28d71fe6,0xa8d7a728,0x27d39fe6,0x1bef28ad,0xa876a835,0x24c5290f,0xa909a59f,0x266ba3bf,0x21e028f6,
0x21e0a728,0x266b28f6,0xa909a3bf,0x24c5a59f,0xa8760000,0x1befa835,0x27d328ad,0xa8d79fe6,0x28d72728,0xa7d31fe6,0x9befa8ad,0x28762835,
0xa4c5a90f,0x2909259f,0xa66b23bf,0xa1e0a8f6,0x23bf290f,0xa8ada728,0x28ad8000,0xa3bf2728,0xa3bfa90f,0x28ad2728,0xa8ad0000,0x23bfa728,
0x23bf290f,0xa8ada728,0x28ad8000,0xa3bf2728,0xa3bfa90f,0x28ad2728,0xa8ad0000,0x23bfa728,0x23bf290f,0xa8ada728,0x28ad8000,0xa3bf2728,
0xa3bfa90f,0x28ad2728,0xa8ad0000,0x23bfa728,0x23bf290f,0xa8ada728,0x28ad8000,0xa3bf2728,0xa3bfa90f,0x28ad2728,0xa8ad0000,0x23bfa728,
0xa4c52728,0x9befa8f6,0x266b28ad,0xa8d7a59f,0xa1e0a90f,0x27d32835,0xa909a3bf,0x28769fe6,0xa876a728,0x29091fe6,0xa7d323bf,0x21e0a835,
0x28d78000,0xa66b259f,0x1befa8ad,0x24c528f6,0x24c5a728,0x1bef28f6,0xa66ba8ad,0x28d7259f,0x21e0290f,0xa7d3a835,0x290923bf,0xa8761fe6,
0x28762728,0xa9099fe6,0x27d3a3bf,0xa1e02835,0xa8d70000,0x266ba59f,0x9bef28ad,0xa4c5a8f6,0x9fe6a90f,0x259f28ad,0xa835a728,0x28f623bf,
0xa8f60000,0x2835a3bf,0xa59f2728,0x1fe6a8ad,0x1fe6290f,0xa59fa8ad,0x28352728,0xa8f6a3bf,0x28f68000,0xa83523bf,0x259fa728,0x9fe628ad,
0x9fe6a90f,0x259f28ad,0xa835a728,0x28f623bf,0xa8f60000,0x2835a3bf,0xa59f2728,0x1fe6a8ad,0x1fe6290f,0xa59fa8ad,0x28352728,0xa8f6a3bf,
0x28f68000,0xa83523bf,0x259fa728,0x9fe628ad,0xa66b2728,0x24c5a835,0xa1e028ad,0x1befa8f6,0xa9090000,0x28d79fe6,0xa87623bf,0x27d3a59f,
0xa7d3a728,0x2876259f,0xa8d7a3bf,0x29091fe6,0x9befa90f,0x21e028f6,0xa4c5a8ad,0x266b2835,0x266ba728,0xa4c52835,0x21e0a8ad,0x9bef28f6,
0x29098000,0xa8d71fe6,0x2876a3bf,0xa7d3259f,0x27d32728,0xa876a59f,0x28d723bf,0xa9099fe6,0x1bef290f,0xa1e0a8f6,0x24c528ad,0xa66ba835,
0xa7288000,0xa728a90f,0x27288000,0x2728290f,0xa7288000,0xa728a90f,0x27288000,0x2728290f,0xa7288000,0xa728a90f,0x27288000,0x2728290f,
0xa7288000,0xa728a90f,0x27288000,0x2728290f,0xa7288000,0xa728a90f,0x27288000,0x2728290f,0xa7288000,0xa728a90f,0x27288000,0x2728290f,
0xa7288000,0xa728a90f,0x27288000,0x2728290f,0xa7288000,0xa728a90f,0x27288000,0x2728290f,0xa909a728,0x21e0a59f,0x287628ad,0xa66b1fe6,
0xa7d38000,0xa4c5a8f6,0x28d723bf,0x1bef2835,0x1befa728,0x28d72835,0xa4c523bf,0xa7d3a8f6,0xa66ba90f,0x28761fe6,0x21e028ad,0xa909a59f,
0x29092728,0xa1e0259f,0xa876a8ad,0x266b9fe6,0x27d38000,0x24c528f6,0xa8d7a3bf,0x9befa835,0x9bef2728,0xa8d7a835,0x24c5a3bf,0x27d328f6,
0x266b290f,0xa8769fe6,0xa1e0a8ad,0x2909259f,0x28358000,0x1fe628ad,0xa8f6a728,0x259fa3bf,0x259f290f,0xa8f6a3bf,0x1fe6a728,0x283528ad,
0xa8358000,0x9fe6a8ad,0x28f62728,0xa59f23bf,0xa59fa90f,0x28f623bf,0x9fe62728,0xa835a8ad,0x28358000,0x1fe628ad,0xa8f6a728,0x259fa3bf,
0x259f290f,0xa8f6a3bf,0x1fe6a728,0x283528ad,0xa8358000,0x9fe6a8ad,0x28f62728,0xa59f23bf,0xa59fa90f,0x28f623bf,0x9fe62728,0xa835a8ad,
0xa8d7a728,0x27d39fe6,0x1bef28ad,0xa876a835,0x24c5290f,0xa909a59f,0x266ba3bf,0x21e028f6,0x21e0a728,0x266b28f6,0xa909a3bf,0x24c5a59f,
0xa8768000,0x1befa835,0x27d328ad,0xa8d79fe6,0x28d72728,0xa7d31fe6,0x9befa8ad,0x28762835,0xa4c5a90f,0x2909259f,0xa66b23bf,0xa1e0a8f6,
0xa1e02728,0xa66ba8f6,0x290923bf,0xa4c5259f,0x28768000,0x9bef2835,0xa7d3a8ad,0x28d71fe6,0xa8ad8000,0x23bfa728,0x23bf290f,0xa8ada728,
0x28ad8000,0xa3bf2728,0xa3bfa90f,0x28ad2728,0xa8ad8000,0x23bfa728,0x23bf290f,0xa8ada728,0x28ad8000,0xa3bf2728,0xa3bfa90f,0x28ad2728,
0xa8ad8000,0x23bfa728,0x23bf290f,0xa8ada728,0x28ad8000,0xa3bf2728,0xa3bfa90f,0x28ad2728,0xa8ad8000,0x23bfa728,0x23bf290f,0xa8ada728,
0x28ad8000,0xa3bf2728,0xa3bfa90f,0x28ad2728,0xa876a728,0x29091fe6,0xa7d323bf,0x21e0a835,0x28d78000,0xa66b259f,0x1befa8ad,0x24c528f6,
0x24c5a728,0x1bef28f6,0xa66ba8ad,0x28d7259f,0x21e0290f,0xa7d3a835,0x290923bf,0xa8761fe6,0x28762728,0xa9099fe6,0x27d3a3bf,0xa1e02835,
0xa8d78000,0x266ba59f,0x9bef28ad,0xa4c5a8f6,0xa4c52728,0x9befa8f6,0x266b28ad,0xa8d7a59f,0xa1e0a90f,0x27d32835,0xa909a3bf,0x28769fe6,
0x28f68000,0xa83523bf,0x259fa728,0x9fe628ad,0x9fe6a90f,0x259f28ad,0xa835a728,0x28f623bf,0xa8f68000,0x2835a3bf,0xa59f2728,0x1fe6a8ad,
0x1fe6290f,0xa59fa8ad,0x28352728,0xa8f6a3bf,0x28f68000,0xa83523bf,0x259fa728,0x9fe628ad,0x9fe6a90f,0x259f28ad,0xa835a728,0x28f623bf,
0xa8f68000,0x2835a3bf,0xa59f2728,0x1fe6a8ad,0x1fe6290f,0xa59fa8ad,0x28352728,0xa8f6a3bf,0xa7d3a728,0x2876259f,0xa8d7a3bf,0x29091fe6,
0x9befa90f,0x21e028f6,0xa4c5a8ad,0x266b2835,0x266ba728,0xa4c52835,0x21e0a8ad,0x9bef28f6,0x29098000,0xa8d71fe6,0x2876a3bf,0xa7d3259f,
0x27d32728,0xa876a59f,0x28d723bf,0xa9099fe6,0x1bef290f,0xa1e0a8f6,0x24c528ad,0xa66ba835,0xa66b2728,0x24c5a835,0xa1e028ad,0x1befa8f6,
0xa9098000,0x28d79fe6,0xa87623bf,0x27d3a59f,0x290f,0x8000a90f,0x290f,0x8000a90f,0x290f,0x8000a90f,0x290f,0x8000a90f,
0x290f,0x8000a90f,0x290f,0x8000a90f,0x290f,0x8000a90f,0x290f,0x8000a90f,0x290f,0x8000a90f,0x290f,0x8000a90f,
0x290f,0x8000a90f,0x290f,0x8000a90f,0x290f,0x8000a90f,0x290f,0x8000a90f,0x290f,0x8000a90f,0x290f,0x8000a90f,
0xa7d32728,0x2876a59f,0xa8d723bf,0x29099fe6,0x9bef290f,0x21e0a8f6,0xa4c528ad,0x266ba835,0xa66ba728,0x24c52835,0xa1e0a8ad,0x1bef28f6,
0xa9090000,0x28d71fe6,0xa876a3bf,0x27d3259f,0x27d3a728,0xa876259f,0x28d7a3bf,0xa9091fe6,0x1befa90f,0xa1e028f6,0x24c5a8ad,0xa66b2835,
0x266b2728,0xa4c5a835,0x21e028ad,0x9befa8f6,0x29098000,0xa8d79fe6,0x287623bf,0xa7d3a59f,0x1fe6a90f,0xa59f28ad,0x2835a728,0xa8f623bf,
0x28f68000,0xa835a3bf,0x259f2728,0x9fe6a8ad,0x9fe6290f,0x259fa8ad,0xa8352728,0x28f6a3bf,0xa8f60000,0x283523bf,0xa59fa728,0x1fe628ad,
0x1fe6a90f,0xa59f28ad,0x2835a728,0xa8f623bf,0x28f68000,0xa835a3bf,0x259f2728,0x9fe6a8ad,0x9fe6290f,0x259fa8ad,0xa8352728,0x28f6a3bf,
0xa8f60000,0x283523bf,0xa59fa728,0x1fe628ad,0xa8762728,0x29099fe6,0xa7d3a3bf,0x21e02835,0x28d78000,0xa66ba59f,0x1bef28ad,0x24c5a8f6,
0xa4c5a728,0x9bef28f6,0x266ba8ad,0xa8d7259f,0xa1e0290f,0x27d3a835,0xa90923bf,0x28761fe6,0x2876a728,0xa9091fe6,0x27d323bf,0xa1e0a835,
0xa8d70000,0x266b259f,0x9befa8ad,0xa4c528f6,0x24c52728,0x1befa8f6,0xa66b28ad,0x28d7a59f,0x21e0a90f,0xa7d32835,0x2909a3bf,0xa8769fe6,
0xa3bf290f,0x28ada728,0xa8ad0000,0x23bf2728,0x23bfa90f,0xa8ad2728,0x28ad8000,0xa3bfa728,0xa3bf290f,0x28ada728,0xa8ad0000,0x23bf2728,
0x23bfa90f,0xa8ad2728,0x28ad8000,0xa3bfa728,0xa3bf290f,0x28ada728,0xa8ad0000,0x23bf2728,0x23bfa90f,0xa8ad2728,0x28ad8000,0xa3bfa728,
0xa3bf290f,0x28ada728,0xa8ad0000,0x23bf2728,0x23bfa90f,0xa8ad2728,0x28ad8000,0xa3bfa728,0xa8d72728,0x27d31fe6,0x1befa8ad,0xa8762835,
0x24c5a90f,0xa909259f,0x266b23bf,0x21e0a8f6,0xa1e0a728,0xa66b28f6,0x2909a3bf,0xa4c5a59f,0x28768000,0x9befa835,0xa7d328ad,0x28d79fe6,
0x28d7a728,0xa7d39fe6,0x9bef28ad,0x2876a835,0xa4c5290f,0x2909a59f,0xa66ba3bf,0xa1e028f6,0x21e02728,0x266ba8f6,0xa90923bf,0x24c5259f,
0xa8760000,0x1bef2835,0x27d3a8ad,0xa8d71fe6,0x259fa90f,0xa8f623bf,0x1fe62728,0x2835a8ad,0xa8350000,0x9fe628ad,0x28f6a728,0xa59fa3bf,
0xa59f290f,0x28f6a3bf,0x9fe6a728,0xa83528ad,0x28358000,0x1fe6a8ad,0xa8f62728,0x259f23bf,0x259fa90f,0xa8f623bf,0x1fe62728,0x2835a8ad,
0xa8350000,0x9fe628ad,0x28f6a728,0xa59fa3bf,0xa59f290f,0x28f6a3bf,0x9fe6a728,0xa83528ad,0x28358000,0x1fe6a8ad,0xa8f62728,0x259f23bf,
0xa9092728,0x21e0259f,0x2876a8ad,0xa66b9fe6,0xa7d30000,0xa4c528f6,0x28d7a3bf,0x1befa835,0x9befa728,0xa8d72835,0x24c523bf,0x27d3a8f6,
0x266ba90f,0xa8761fe6,0xa1e028ad,0x2909a59f,0x2909a728,0xa1e0a59f,0xa87628ad,0x266b1fe6,0x27d38000,0x24c5a8f6,0xa8d723bf,0x9bef2835,
0x1bef2728,0x28d7a835,0xa4c5a3bf,0xa7d328f6,0xa66b290f,0x28769fe6,0x21e0a8ad,0xa909259f,0xa90f8000,0x290f8000,0xa90f8000,0x290f8000,
0xa90f8000,0x290f8000,0xa90f8000,0x290f8000,0xa90f8000,0x290f8000,0xa90f8000,0x290f8000,0xa90f8000,0x290f8000,0xa90f8000,0x290f8000,
0xa90f8000,0x290f8000,0xa90f8000,0x290f8000,0xa90f8000,0x290f8000,0xa90f8000,0x290f8000,0xa90f8000,0x290f8000,0xa90f8000,0x290f8000,
0xa90f8000,0x290f8000,0xa90f8000,0x290f8000,0xa66ba728,0x24c52835,0xa1e0a8ad,0x1bef28f6,0xa9098000,0x28d71fe6,0xa876a3bf,0x27d3259f,
0x27d3a728,0xa876259f,0x28d7a3bf,0xa9091fe6,0x1befa90f,0xa1e028f6,0x24c5a8ad,0xa66b2835,0x266b2728,0xa4c5a835,0x21e028ad,0x9befa8f6,
0x29098000,0xa8d79fe6,0x287623bf,0xa7d3a59f,0xa7d32728,0x2876a59f,0xa8d723bf,0x29099fe6,0x9bef290f,0x21e0a8f6,0xa4c528ad,0x266ba835,
0x28f68000,0xa835a3bf,0x259f2728,0x9fe6a8ad,0x9fe6290f,0x259fa8ad,0xa8352728,0x28f6a3bf,0xa8f68000,0x283523bf,0xa59fa728,0x1fe628ad,
0x1fe6a90f,0xa59f28ad,0x2835a728,0xa8f623bf,0x28f68000,0xa835a3bf,0x259f2728,0x9fe6a8ad,0x9fe6290f,0x259fa8ad,0xa8352728,0x28f6a3bf,
0xa8f68000,0x283523bf,0xa59fa728,0x1fe628ad,0x1fe6a90f,0xa59f28ad,0x2835a728,0xa8f623bf,0xa4c5a728,0x9bef28f6,0x266ba8ad,0xa8d7259f,
0xa1e0290f,0x27d3a835,0xa90923bf,0x28761fe6,0x2876a728,0xa9091fe6,0x27d323bf,0xa1e0a835,0xa8d78000,0x266b259f,0x9befa8ad,0xa4c528f6,
0x24c52728,0x1befa8f6,0xa66b28ad,0x28d7a59f,0x21e0a90f,0xa7d32835,0x2909a3bf,0xa8769fe6,0xa8762728,0x29099fe6,0xa7d3a3bf,0x21e02835,
0x28d78000,0xa66ba59f,0x1bef28ad,0x24c5a8f6,0xa8ad8000,0x23bf2728,0x23bfa90f,0xa8ad2728,0x28ad8000,0xa3bfa728,0xa3bf290f,0x28ada728,
0xa8ad8000,0x23bf2728,0x23bfa90f,0xa8ad2728,0x28ad8000,0xa3bfa728,0xa3bf290f,0x28ada728,0xa8ad8000,0x23bf2728,0x23bfa90f,0xa8ad2728,
0x28ad8000,0xa3bfa728,0xa3bf290f,0x28ada728,0xa8ad8000,0x23bf2728,0x23bfa90f,0xa8ad2728,0x28ad8000,0xa3bfa728,0xa3bf290f,0x28ada728,
0xa1e0a728,0xa66b28f6,0x2909a3bf,0xa4c5a59f,0x28768000,0x9befa835,0xa7d328ad,0x28d79fe6,0x28d7a728,0xa7d39fe6,0x9bef28ad,0x2876a835,
0xa4c5290f,0x2909a59f,0xa66ba3bf,0xa1e028f6,0x21e02728,0x266ba8f6,0xa90923bf,0x24c5259f,0xa8768000,0x1bef2835,0x27d3a8ad,0xa8d71fe6,
0xa8d72728,0x27d31fe6,0x1befa8ad,0xa8762835,0x24c5a90f,0xa909259f,0x266b23bf,0x21e0a8f6,0x28358000,0x1fe6a8ad,0xa8f62728,0x259f23bf,
0x259fa90f,0xa8f623bf,0x1fe62728,0x2835a8ad,0xa8358000,0x9fe628ad,0x28f6a728,0xa59fa3bf,0xa59f290f,0x28f6a3bf,0x9fe6a728,0xa83528ad,
0x28358000,0x1fe6a8ad,0xa8f62728,0x259f23bf,0x259fa90f,0xa8f623bf,0x1fe62728,0x2835a8ad,0xa8358000,0x9fe628ad,0x28f6a728,0xa59fa3bf,
0xa59f290f,0x28f6a3bf,0x9fe6a728,0xa83528ad,0x9befa728,0xa8d72835,0x24c523bf,0x27d3a8f6,0x266ba90f,0xa8761fe6,0xa1e028ad,0x2909a59f,
0x2909a728,0xa1e0a59f,0xa87628ad,0x266b1fe6,0x27d38000,0x24c5a8f6,0xa8d723bf,0x9bef2835,0x1bef2728,0x28d7a835,0xa4c5a3bf,0xa7d328f6,
0xa66b290f,0x28769fe6,0x21e0a8ad,0xa909259f,0xa9092728,0x21e0259f,0x2876a8ad,0xa66b9fe6,0xa7d38000,0xa4c528f6,0x28d7a3bf,0x1befa835,
0xa728290f,0x27288000,0x2728a90f,0xa7280000,0xa728290f,0x27288000,0x2728a90f,0xa7280000,0xa728290f,0x27288000,0x2728a90f,0xa7280000,
0xa728290f,0x27288000,0x2728a90f,0xa7280000,0xa728290f,0x27288000,0x2728a90f,0xa7280000,0xa728290f,0x27288000,0x2728a90f,0xa7280000,
0xa728290f,0x27288000,0x2728a90f,0xa7280000,0xa728290f,0x27288000,0x2728a90f,0xa7280000,0xa9092728,0xa1e02835,0x2876a3bf,0x266ba8f6,
0xa7d3290f,0x24c51fe6,0x28d7a8ad,0x9befa59f,0x1befa728,0xa8d7259f,0xa4c528ad,0x27d39fe6,0xa66b0000,0xa87628f6,0x21e023bf,0x2909a835,
0x2909a728,0x21e0a835,0xa87623bf,0xa66b28f6,0x27d3a90f,0xa4c59fe6,0xa8d728ad,0x1bef259f,0x9bef2728,0x28d7a59f,0x24c5a8ad,0xa7d31fe6,
0x266b8000,0x2876a8f6,0xa1e0a3bf,0xa9092835,0x2835a90f,0x9fe6a3bf,0xa8f62728,0xa59f28ad,0x259f8000,0x28f6a8ad,0x1fe6a728,0xa83523bf,
0xa835290f,0x1fe623bf,0x28f6a728,0x259fa8ad,0xa59f0000,0xa8f628ad,0x9fe62728,0x2835a3bf,0x2835a90f,0x9fe6a3bf,0xa8f62728,0xa59f28ad,
0x259f8000,0x28f6a8ad,0x1fe6a728,0xa83523bf,0xa835290f,0x1fe623bf,0x28f6a728,0x259fa8ad,0xa59f0000,0xa8f628ad,0x9fe62728,0x2835a3bf,
0xa8d72728,0xa7d328f6,0x1bef23bf,0x2876a59f,0x24c58000,0x2909a835,0x266ba8ad,0xa1e09fe6,0x21e0a728,0xa66b1fe6,0xa90928ad,0xa4c52835,
0xa876290f,0x9bef259f,0x27d3a3bf,0x28d7a8f6,0x28d7a728,0x27d3a8f6,0x9befa3bf,0xa876259f,0xa4c50000,0xa9092835,0xa66b28ad,0x21e01fe6,
0xa1e02728,0x266b9fe6,0x2909a8ad,0x24c5a835,0x2876a90f,0x1befa59f,0xa7d323bf,0xa8d728f6,0xa8ad290f,0xa3bf2728,0x23bf8000,0x28ada728,
0x28ada90f,0x23bfa728,0xa3bf0000,0xa8ad2728,0xa8ad290f,0xa3bf2728,0x23bf8000,0x28ada728,0x28ada90f,0x23bfa728,0xa3bf0000,0xa8ad2728,
0xa8ad290f,0xa3bf2728,0x23bf8000,0x28ada728,0x28ada90f,0x23bfa728,0xa3bf0000,0xa8ad2728,0xa8ad290f,0xa3bf2728,0x23bf8000,0x28ada728,
0x28ada90f,0x23bfa728,0xa3bf0000,0xa8ad2728,0xa8762728,0xa90928f6,0xa7d328ad,0xa1e0259f,0x28d7a90f,0x266ba835,0x1befa3bf,0xa4c51fe6,
0x24c5a728,0x9bef9fe6,0xa66b23bf,0xa8d72835,0x21e08000,0x27d3a59f,0x2909a8ad,0x2876a8f6,0x2876a728,0x2909a8f6,0x27d3a8ad,0x21e0a59f,
0xa8d7290f,0xa66b2835,0x9bef23bf,0x24c59fe6,0xa4c52728,0x1bef1fe6,0x266ba3bf,0x28d7a835,0xa1e00000,0xa7d3259f,0xa90928ad,0xa87628f6,
0x28f6a90f,0x2835a8ad,0x259fa728,0x1fe6a3bf,0x9fe60000,0xa59f23bf,0xa8352728,0xa8f628ad,0xa8f6290f,0xa83528ad,0xa59f2728,0x9fe623bf,
0x1fe68000,0x259fa3bf,0x2835a728,0x28f6a8ad,0x28f6a90f,0x2835a8ad,0x259fa728,0x1fe6a3bf,0x9fe60000,0xa59f23bf,0xa8352728,0xa8f628ad,
0xa8f6290f,0xa83528ad,0xa59f2728,0x9fe623bf,0x1fe68000,0x259fa3bf,0x2835a728,0x28f6a8ad,0xa7d32728,0xa8762835,0xa8d728ad,0xa90928f6,
0x9bef0000,0xa1e01fe6,0xa4c523bf,0xa66b259f,0x266ba728,0x24c5a59f,0x21e0a3bf,0x1bef9fe6,0x2909a90f,0x28d7a8f6,0x2876a8ad,0x27d3a835,
0x27d3a728,0x2876a835,0x28d7a8ad,0x2909a8f6,0x1bef8000,0x21e09fe6,0x24c5a3bf,0x266ba59f,0xa66b2728,0xa4c5259f,0xa1e023bf,0x9bef1fe6,
0xa909290f,0xa8d728f6,0xa87628ad,0xa7d32835,0xa7288000,0xa728290f,0x27288000,0x2728a90f,0xa7288000,0xa728290f,0x27288000,0x2728a90f,
0xa7288000,0xa728290f,0x27288000,0x2728a90f,0xa7288000,0xa728290f,0x27288000,0x2728a90f,0xa7288000,0xa728290f,0x27288000,0x2728a90f,
0xa7288000,0xa728290f,0x27288000,0x2728a90f,0xa7288000,0xa728290f,0x27288000,0x2728a90f,0xa7288000,0xa728290f,0x27288000,0x2728a90f,
0x1befa728,0xa8d7259f,0xa4c528ad,0x27d39fe6,0xa66b8000,0xa87628f6,0x21e023bf,0x2909a835,0x2909a728,0x21e0a835,0xa87623bf,0xa66b28f6,
0x27d3a90f,0xa4c59fe6,0xa8d728ad,0x1bef259f,0x9bef2728,0x28d7a59f,0x24c5a8ad,0xa7d31fe6,0x266b8000,0x2876a8f6,0xa1e0a3bf,0xa9092835,
0xa9092728,0xa1e02835,0x2876a3bf,0x266ba8f6,0xa7d3290f,0x24c51fe6,0x28d7a8ad,0x9befa59f,0x259f8000,0x28f6a8ad,0x1fe6a728,0xa83523bf,
0xa835290f,0x1fe623bf,0x28f6a728,0x259fa8ad,0xa59f8000,0xa8f628ad,0x9fe62728,0x2835a3bf,0x2835a90f,0x9fe6a3bf,0xa8f62728,0xa59f28ad,
0x259f8000,0x28f6a8ad,0x1fe6a728,0xa83523bf,0xa835290f,0x1fe623bf,0x28f6a728,0x259fa8ad,0xa59f8000,0xa8f628ad,0x9fe62728,0x2835a3bf,
0x2835a90f,0x9fe6a3bf,0xa8f62728,0xa59f28ad,0x21e0a728,0xa66b1fe6,0xa90928ad,0xa4c52835,0xa876290f,0x9bef259f,0x27d3a3bf,0x28d7a8f6,
0x28d7a728,0x27d3a8f6,0x9befa3bf,0xa876259f,0xa4c58000,0xa9092835,0xa66b28ad,0x21e01fe6,0xa1e02728,0x266b9fe6,0x2909a8ad,0x24c5a835,
0x2876a90f,0x1befa59f,0xa7d323bf,0xa8d728f6,0xa8d72728,0xa7d328f6,0x1bef23bf,0x2876a59f,0x24c58000,0x2909a835,0x266ba8ad,0xa1e09fe6,
0xa3bf8000,0xa8ad2728,0xa8ad290f,0xa3bf2728,0x23bf8000,0x28ada728,0x28ada90f,0x23bfa728,0xa3bf8000,0xa8ad2728,0xa8ad290f,0xa3bf2728,
0x23bf8000,0x28ada728,0x28ada90f,0x23bfa728,0xa3bf8000,0xa8ad2728,0xa8ad290f,0xa3bf2728,0x23bf8000,0x28ada728,0x28ada90f,0x23bfa728,
0xa3bf8000,0xa8ad2728,0xa8ad290f,0xa3bf2728,0x23bf8000,0x28ada728,0x28ada90f,0x23bfa728,0x24c5a728,0x9bef9fe6,0xa66b23bf,0xa8d72835,
0x21e08000,0x27d3a59f,0x2909a8ad,0x2876a8f6,0x2876a728,0x2909a8f6,0x27d3a8ad,0x21e0a59f,0xa8d7290f,0xa66b2835,0x9bef23bf,0x24c59fe6,
0xa4c52728,0x1bef1fe6,0x266ba3bf,0x28d7a835,0xa1e08000,0xa7d3259f,0xa90928ad,0xa87628f6,0xa8762728,0xa90928f6,0xa7d328ad,0xa1e0259f,
0x28d7a90f,0x266ba835,0x1befa3bf,0xa4c51fe6,0x1fe68000,0x259fa3bf,0x2835a728,0x28f6a8ad,0x28f6a90f,0x2835a8ad,0x259fa728,0x1fe6a3bf,
0x9fe68000,0xa59f23bf,0xa8352728,0xa8f628ad,0xa8f6290f,0xa83528ad,0xa59f2728,0x9fe623bf,0x1fe68000,0x259fa3bf,0x2835a728,0x28f6a8ad,
0x28f6a90f,0x2835a8ad,0x259fa728,0x1fe6a3bf,0x9fe68000,0xa59f23bf,0xa8352728,0xa8f628ad,0xa8f6290f,0xa83528ad,0xa59f2728,0x9fe623bf,
0x266ba728,0x24c5a59f,0x21e0a3bf,0x1bef9fe6,0x2909a90f,0x28d7a8f6,0x2876a8ad,0x27d3a835,0x27d3a728,0x2876a835,0x28d7a8ad,0x2909a8f6,
0x1bef8000,0x21e09fe6,0x24c5a3bf,0x266ba59f,0xa66b2728,0xa4c5259f,0xa1e023bf,0x9bef1fe6,0xa909290f,0xa8d728f6,0xa87628ad,0xa7d32835,
0xa7d32728,0xa8762835,0xa8d728ad,0xa90928f6,0x9bef8000,0xa1e01fe6,0xa4c523bf,0xa66b259f,0x31a831a8,0x31a831a8,0x31a831a8,0x31a831a8,
0x318c31a8,0x30b4313a,0x2e493000,0x286a2c54,0x313a31a8,0x2c543000,0xac540000,0xb13ab000,0x30b431a8,0xa86a2c54,0xb18cb000,0xae49b13a,
0x300031a8,0xb0000000,0xb000b1a8,0x30008000,0x2e4931a8,0xb18cac54,0x286ab000,0x30b4313a,0x2c5431a8,0xb13ab000,0x313a8000,0xac543000,
0x286a31a8,0xae49b13a,0x30b43000,0xb18cac54,0x80008000,0x80008000,0x80008000,0x80008000,0xa86a8000,0xae49ac54,0xb0b4b000,0xb18cb13a,
0xac548000,0xb13ab000,0xb13ab1a8,0xac54b000,0xae498000,0xb18cb13a,0xa86ab000,0x30b42c54,0xb0008000,0xb000b1a8,0x30008000,0x300031a8,
0xb0b48000,0xa86ab13a,0x318c3000,0xae492c54,0xb13a8000,0x2c54b000,0x2c5431a8,0xb13ab000,0xb18c8000,0x30b4ac54,0xae493000,0x286ab13a,
0x31a8,0x8000b1a8,0x31a8,0x8000b1a8,0xa86a31a8,0x2e49b13a,0xb0b43000,0x318cac54,0xac5431a8,0x313ab000,0xb13a0000,0x2c543000,
0xae4931a8,0x318cac54,0xa86ab000,0xb0b4313a,0xb00031a8,0x30008000,0x3000b1a8,0xb0000000,0xb0b431a8,0x286a2c54,0x318cb000,0x2e49b13a,
0xb13a31a8,0xac543000,0x2c548000,0x313ab000,0xb18c31a8,0xb0b4313a,0xae493000,0xa86a2c54,0xb1a88000,0x31a88000,0xb1a88000,0x31a88000,
0xb18c8000,0x30b42c54,0xae49b000,0x286a313a,0xb13a8000,0x2c543000,0x2c54b1a8,0xb13a3000,0xb0b48000,0xa86a313a,0x318cb000,0xae49ac54,
0xb0008000,0xb00031a8,0x30008000,0x3000b1a8,0xae498000,0xb18c313a,0xa86a3000,0x30b4ac54,0xac548000,0xb13a3000,0xb13a31a8,0xac543000,
0xa86a8000,0xae492c54,0xb0b43000,0xb18c313a,0xb1a831a8,0xb1a831a8,0xb1a831a8,0xb1a831a8,0xb18c31a8,0xb0b4313a,0xae493000,0xa86a2c54,
0xb13a31a8,0xac543000,0x2c540000,0x313ab000,0xb0b431a8,0x286a2c54,0x318cb000,0x2e49b13a,0xb00031a8,0x30000000,0x3000b1a8,0xb0008000,
0xae4931a8,0x318cac54,0xa86ab000,0xb0b4313a,0xac5431a8,0x313ab000,0xb13a8000,0x2c543000,0xa86a31a8,0x2e49b13a,0xb0b43000,0x318cac54,
0x80008000,0x80008000,0x80008000,0x80008000,0x286a8000,0x2e49ac54,0x30b4b000,0x318cb13a,0x2c548000,0x313ab000,0x313ab1a8,0x2c54b000,
0x2e498000,0x318cb13a,0x286ab000,0xb0b42c54,0x30008000,0x3000b1a8,0xb0008000,0xb00031a8,0x30b48000,0x286ab13a,0xb18c3000,0x2e492c54,
0x313a8000,0xac54b000,0xac5431a8,0x313ab000,0x318c8000,0xb0b4ac54,0x2e493000,0xa86ab13a,0x800031a8,0xb1a8,0x800031a8,0xb1a8,
0x286a31a8,0xae49b13a,0x30b43000,0xb18cac54,0x2c5431a8,0xb13ab000,0x313a0000,0xac543000,0x2e4931a8,0xb18cac54,0x286ab000,0x30b4313a,
0x300031a8,0xb0008000,0xb000b1a8,0x30000000,0x30b431a8,0xa86a2c54,0xb18cb000,0xae49b13a,0x313a31a8,0x2c543000,0xac548000,0xb13ab000,
0x318c31a8,0x30b4313a,0x2e493000,0x286a2c54,0x31a88000,0xb1a88000,0x31a88000,0xb1a88000,0x318c8000,0xb0b42c54,0x2e49b000,0xa86a313a,
0x313a8000,0xac543000,0xac54b1a8,0x313a3000,0x30b48000,0x286a313a,0xb18cb000,0x2e49ac54,0x30008000,0x300031a8,0xb0008000,0xb000b1a8,
0x2e498000,0x318c313a,0x286a3000,0xb0b4ac54,0x2c548000,0x313a3000,0x313a31a8,0x2c543000,0x286a8000,0x2e492c54,0x30b43000,0x318c313a,
0x0,0x0,0x0,0x0,0x286a0000,0x2e492c54,0x30b43000,0x318c313a,0x2c540000,0x313a3000,0x313a31a8,0x2c543000,
0x2e490000,0x318c313a,0x286a3000,0xb0b4ac54,0x30000000,0x300031a8,0xb0000000,0xb000b1a8,0x30b40000,0x286a313a,0xb18cb000,0x2e49ac54,
0x313a0000,0xac543000,0xac54b1a8,0x313a3000,0x318c0000,0xb0b42c54,0x2e49b000,0xa86a313a,0x31a831a8,0x31a831a8,0x31a831a8,0x31a831a8,
0x318c31a8,0x30b4313a,0x2e493000,0x286a2c54,0x313a31a8,0x2c543000,0xac540000,0xb13ab000,0x30b431a8,0xa86a2c54,0xb18cb000,0xae49b13a,
0x300031a8,0xb0000000,0xb000b1a8,0x30008000,0x2e4931a8,0xb18cac54,0x286ab000,0x30b4313a,0x2c5431a8,0xb13ab000,0x313a8000,0xac543000,
0x286a31a8,0xae49b13a,0x30b43000,0xb18cac54,0x31a80000,0xb1a80000,0x31a80000,0xb1a80000,0x318c0000,0xb0b4ac54,0x2e493000,0xa86ab13a,
0x313a0000,0xac54b000,0xac5431a8,0x313ab000,0x30b40000,0x286ab13a,0xb18c3000,0x2e492c54,0x30000000,0x3000b1a8,0xb0000000,0xb00031a8,
0x2e490000,0x318cb13a,0x286ab000,0xb0b42c54,0x2c540000,0x313ab000,0x313ab1a8,0x2c54b000,0x286a0000,0x2e49ac54,0x30b4b000,0x318cb13a,
0x31a8,0x8000b1a8,0x31a8,0x8000b1a8,0xa86a31a8,0x2e49b13a,0xb0b43000,0x318cac54,0xac5431a8,0x313ab000,0xb13a0000,0x2c543000,
0xae4931a8,0x318cac54,0xa86ab000,0xb0b4313a,0xb00031a8,0x30008000,0x3000b1a8,0xb0000000,0xb0b431a8,0x286a2c54,0x318cb000,0x2e49b13a,
0xb13a31a8,0xac543000,0x2c548000,0x313ab000,0xb18c31a8,0xb0b4313a,0xae493000,0xa86a2c54,0x0,0x0,0x0,0x0,
0xa86a0000,0xae492c54,0xb0b43000,0xb18c313a,0xac540000,0xb13a3000,0xb13a31a8,0xac543000,0xae490000,0xb18c313a,0xa86a3000,0x30b4ac54,
0xb0000000,0xb00031a8,0x30000000,0x3000b1a8,0xb0b40000,0xa86a313a,0x318cb000,0xae49ac54,0xb13a0000,0x2c543000,0x2c54b1a8,0xb13a3000,
0xb18c0000,0x30b42c54,0xae49b000,0x286a313a,0xb1a831a8,0xb1a831a8,0xb1a831a8,0xb1a831a8,0xb18c31a8,0xb0b4313a,0xae493000,0xa86a2c54,
0xb13a31a8,0xac543000,0x2c540000,0x313ab000,0xb0b431a8,0x286a2c54,0x318cb000,0x2e49b13a,0xb00031a8,0x30000000,0x3000b1a8,0xb0008000,
0xae4931a8,0x318cac54,0xa86ab000,0xb0b4313a,0xac5431a8,0x313ab000,0xb13a8000,0x2c543000,0xa86a31a8,0x2e49b13a,0xb0b43000,0x318cac54,
0xb1a80000,0x31a80000,0xb1a80000,0x31a80000,0xb18c0000,0x30b4ac54,0xae493000,0x286ab13a,0xb13a0000,0x2c54b000,0x2c5431a8,0xb13ab000,
0xb0b40000,0xa86ab13a,0x318c3000,0xae492c54,0xb0000000,0xb000b1a8,0x30000000,0x300031a8,0xae490000,0xb18cb13a,0xa86ab000,0x30b42c54,
0xac540000,0xb13ab000,0xb13ab1a8,0xac54b000,0xa86a0000,0xae49ac54,0xb0b4b000,0xb18cb13a,0x800031a8,0xb1a8,0x800031a8,0xb1a8,
0x286a31a8,0xae49b13a,0x30b43000,0xb18cac54,0x2c5431a8,0xb13ab000,0x313a0000,0xac543000,0x2e4931a8,0xb18cac54,0x286ab000,0x30b4313a,
0x300031a8,0xb0008000,0xb000b1a8,0x30000000,0x30b431a8,0xa86a2c54,0xb18cb000,0xae49b13a,0x313a31a8,0x2c543000,0xac548000,0xb13ab000,
0x318c31a8,0x30b4313a,0x2e493000,0x286a2c54,0x31a831a8,0x31a831a8,0x31a831a8,0x31a831a8,0xa86a0000,0xae49ac54,0xb0b4b000,0xb18cb13a,
0xb13ab1a8,0xac54b000,0x2c548000,0x313a3000,0x2e498000,0x318c313a,0x286a3000,0xb0b4ac54,0x300031a8,0xb0000000,0xb000b1a8,0x30008000,
0xb0b40000,0xa86ab13a,0x318c3000,0xae492c54,0xac54b1a8,0x313a3000,0xb13a0000,0x2c54b000,0x318c8000,0xb0b42c54,0x2e49b000,0xa86a313a,
0x80008000,0x80008000,0x80008000,0x80008000,0xb18cb1a8,0xb0b4b13a,0xae49b000,0xa86aac54,0x2c548000,0x313a3000,0x313a31a8,0x2c543000,
0x30b431a8,0xa86a2c54,0xb18cb000,0xae49b13a,0xb0008000,0xb000b1a8,0x30008000,0x300031a8,0xae49b1a8,0x318c2c54,0xa86a3000,0xb0b4b13a,
0x313a8000,0xac543000,0xac54b1a8,0x313a3000,0x286a31a8,0xae49b13a,0x30b43000,0xb18cac54,0x31a8,0x8000b1a8,0x31a8,0x8000b1a8,
0xb18c0000,0x30b42c54,0xae49b000,0x286a313a,0x2c54b1a8,0xb13a3000,0x313a8000,0xac54b000,0x30b48000,0x286ab13a,0xb18c3000,0x2e492c54,
0xb00031a8,0x30008000,0x3000b1a8,0xb0000000,0xae490000,0xb18c313a,0xa86a3000,0x30b4ac54,0x313ab1a8,0x2c54b000,0xac540000,0xb13a3000,
0x286a8000,0x2e49ac54,0x30b4b000,0x318cb13a,0xb1a88000,0x31a88000,0xb1a88000,0x31a88000,0x286ab1a8,0xae49313a,0x30b4b000,0xb18c2c54,
0x313a8000,0xac54b000,0xac5431a8,0x313ab000,0xae4931a8,0x318cac54,0xa86ab000,0xb0b4313a,0xb0008000,0xb00031a8,0x30008000,0x3000b1a8,
0x30b4b1a8,0xa86aac54,0xb18c3000,0xae49313a,0x2c548000,0x313ab000,0x313ab1a8,0x2c54b000,0xb18c31a8,0xb0b4313a,0xae493000,0xa86a2c54,
0xb1a831a8,0xb1a831a8,0xb1a831a8,0xb1a831a8,0x286a0000,0x2e49ac54,0x30b4b000,0x318cb13a,0x313ab1a8,0x2c54b000,0xac548000,0xb13a3000,
0xae498000,0xb18c313a,0xa86a3000,0x30b4ac54,0xb00031a8,0x30000000,0x3000b1a8,0xb0008000,0x30b40000,0x286ab13a,0xb18c3000,0x2e492c54,
0x2c54b1a8,0xb13a3000,0x313a0000,0xac54b000,0xb18c8000,0x30b42c54,0xae49b000,0x286a313a,0x80008000,0x80008000,0x80008000,0x80008000,
0x318cb1a8,0x30b4b13a,0x2e49b000,0x286aac54,0xac548000,0xb13a3000,0xb13a31a8,0xac543000,0xb0b431a8,0x286a2c54,0x318cb000,0x2e49b13a,
0x30008000,0x3000b1a8,0xb0008000,0xb00031a8,0x2e49b1a8,0xb18c2c54,0x286a3000,0x30b4b13a,0xb13a8000,0x2c543000,0x2c54b1a8,0xb13a3000,
0xa86a31a8,0x2e49b13a,0xb0b43000,0x318cac54,0x800031a8,0xb1a8,0x800031a8,0xb1a8,0x318c0000,0xb0b42c54,0x2e49b000,0xa86a313a,
0xac54b1a8,0x313a3000,0xb13a8000,0x2c54b000,0xb0b48000,0xa86ab13a,0x318c3000,0xae492c54,0x300031a8,0xb0008000,0xb000b1a8,0x30000000,
0x2e490000,0x318c313a,0x286a3000,0xb0b4ac54,0xb13ab1a8,0xac54b000,0x2c540000,0x313a3000,0xa86a8000,0xae49ac54,0xb0b4b000,0xb18cb13a,
0x31a88000,0xb1a88000,0x31a88000,0xb1a88000,0xa86ab1a8,0x2e49313a,0xb0b4b000,0x318c2c54,0xb13a8000,0x2c54b000,0x2c5431a8,0xb13ab000,
0x2e4931a8,0xb18cac54,0x286ab000,0x30b4313a,0x30008000,0x300031a8,0xb0008000,0xb000b1a8,0xb0b4b1a8,0x286aac54,0x318c3000,0x2e49313a,
0xac548000,0xb13ab000,0xb13ab1a8,0xac54b000,0x318c31a8,0x30b4313a,0x2e493000,0x286a2c54,0x0,0x0,0x0,0x0,
0x318c31a8,0x30b4313a,0x2e493000,0x286a2c54,0xac540000,0xb13ab000,0xb13ab1a8,0xac54b000,0xb0b4b1a8,0x286aac54,0x318c3000,0x2e49313a,
0x30000000,0x300031a8,0xb0000000,0xb000b1a8,0x2e4931a8,0xb18cac54,0x286ab000,0x30b4313a,0xb13a0000,0x2c54b000,0x2c5431a8,0xb13ab000,
0xa86ab1a8,0x2e49313a,0xb0b4b000,0x318c2c54,0x31a831a8,0x31a831a8,0x31a831a8,0x31a831a8,0xa86a0000,0xae49ac54,0xb0b4b000,0xb18cb13a,
0xb13ab1a8,0xac54b000,0x2c548000,0x313a3000,0x2e498000,0x318c313a,0x286a3000,0xb0b4ac54,0x300031a8,0xb0000000,0xb000b1a8,0x30008000,
0xb0b40000,0xa86ab13a,0x318c3000,0xae492c54,0xac54b1a8,0x313a3000,0xb13a0000,0x2c54b000,0x318c8000,0xb0b42c54,0x2e49b000,0xa86a313a,
0x31a80000,0xb1a80000,0x31a80000,0xb1a80000,0xa86a31a8,0x2e49b13a,0xb0b43000,0x318cac54,0xb13a0000,0x2c543000,0x2c54b1a8,0xb13a3000,
0x2e49b1a8,0xb18c2c54,0x286a3000,0x30b4b13a,0x30000000,0x3000b1a8,0xb0000000,0xb00031a8,0xb0b431a8,0x286a2c54,0x318cb000,0x2e49b13a,
0xac540000,0xb13a3000,0xb13a31a8,0xac543000,0x318cb1a8,0x30b4b13a,0x2e49b000,0x286aac54,0x31a8,0x8000b1a8,0x31a8,0x8000b1a8,
0xb18c0000,0x30b42c54,0xae49b000,0x286a313a,0x2c54b1a8,0xb13a3000,0x313a8000,0xac54b000,0x30b48000,0x286ab13a,0xb18c3000,0x2e492c54,
0xb00031a8,0x30008000,0x3000b1a8,0xb0000000,0xae490000,0xb18c313a,0xa86a3000,0x30b4ac54,0x313ab1a8,0x2c54b000,0xac540000,0xb13a3000,
0x286a8000,0x2e49ac54,0x30b4b000,0x318cb13a,0x0,0x0,0x0,0x0,0xb18c31a8,0xb0b4313a,0xae493000,0xa86a2c54,
0x2c540000,0x313ab000,0x313ab1a8,0x2c54b000,0x30b4b1a8,0xa86aac54,0xb18c3000,0xae49313a,0xb0000000,0xb00031a8,0x30000000,0x3000b1a8,
0xae4931a8,0x318cac54,0xa86ab000,0xb0b4313a,0x313a0000,0xac54b000,0xac5431a8,0x313ab000,0x286ab1a8,0xae49313a,0x30b4b000,0xb18c2c54,
0xb1a831a8,0xb1a831a8,0xb1a831a8,0xb1a831a8,0x286a0000,0x2e49ac54,0x30b4b000,0x318cb13a,0x313ab1a8,0x2c54b000,0xac548000,0xb13a3000,
0xae498000,0xb18c313a,0xa86a3000,0x30b4ac54,0xb00031a8,0x30000000,0x3000b1a8,0xb0008000,0x30b40000,0x286ab13a,0xb18c3000,0x2e492c54,
0x2c54b1a8,0xb13a3000,0x313a0000,0xac54b000,0xb18c8000,0x30b42c54,0xae49b000,0x286a313a,0xb1a80000,0x31a80000,0xb1a80000,0x31a80000,
0x286a31a8,0xae49b13a,0x30b43000,0xb18cac54,0x313a0000,0xac543000,0xac54b1a8,0x313a3000,0xae49b1a8,0x318c2c54,0xa86a3000,0xb0b4b13a,
0xb0000000,0xb000b1a8,0x30000000,0x300031a8,0x30b431a8,0xa86a2c54,0xb18cb000,0xae49b13a,0x2c540000,0x313a3000,0x313a31a8,0x2c543000,
0xb18cb1a8,0xb0b4b13a,0xae49b000,0xa86aac54,0x800031a8,0xb1a8,0x800031a8,0xb1a8,0x318c0000,0xb0b42c54,0x2e49b000,0xa86a313a,
0xac54b1a8,0x313a3000,0xb13a8000,0x2c54b000,0xb0b48000,0xa86ab13a,0x318c3000,0xae492c54,0x300031a8,0xb0008000,0xb000b1a8,0x30000000,
0x2e490000,0x318c313a,0x286a3000,0xb0b4ac54,0xb13ab1a8,0xac54b000,0x2c540000,0x313a3000,0xa86a8000,0xae49ac54,0xb0b4b000,0xb18cb13a,
0x31a831a8,0x31a831a8,0x31a831a8,0x31a831a8,0xb18cb1a8,0xb0b4b13a,0xae49b000,0xa86aac54,0x313a31a8,0x2c543000,0xac540000,0xb13ab000,
0xb0b4b1a8,0x286aac54,0x318c3000,0x2e49313a,0x300031a8,0xb0000000,0xb000b1a8,0x30008000,0xae49b1a8,0x318c2c54,0xa86a3000,0xb0b4b13a,
0x2c5431a8,0xb13ab000,0x313a8000,0xac543000,0xa86ab1a8,0x2e49313a,0xb0b4b000,0x318c2c54,0x80008000,0x80008000,0x80008000,0x80008000,
0x286a8000,0x2e492c54,0x30b43000,0x318c313a,0xac548000,0xb13ab000,0xb13ab1a8,0xac54b000,0x2e498000,0x318c313a,0x286a3000,0xb0b4ac54,
0xb0008000,0xb000b1a8,0x30008000,0x300031a8,0x30b48000,0x286a313a,0xb18cb000,0x2e49ac54,0xb13a8000,0x2c54b000,0x2c5431a8,0xb13ab000,
0x318c8000,0xb0b42c54,0x2e49b000,0xa86a313a,0x31a8,0x8000b1a8,0x31a8,0x8000b1a8,0x286ab1a8,0xae49313a,0x30b4b000,0xb18c2c54,
0xac5431a8,0x313ab000,0xb13a0000,0x2c543000,0x2e49b1a8,0xb18c2c54,0x286a3000,0x30b4b13a,0xb00031a8,0x30008000,0x3000b1a8,0xb0000000,
0x30b4b1a8,0xa86aac54,0xb18c3000,0xae49313a,0xb13a31a8,0xac543000,0x2c548000,0x313ab000,0x318cb1a8,0x30b4b13a,0x2e49b000,0x286aac54,
0xb1a88000,0x31a88000,0xb1a88000,0x31a88000,0x318c8000,0xb0b4ac54,0x2e493000,0xa86ab13a,0xb13a8000,0x2c543000,0x2c54b1a8,0xb13a3000,
0x30b48000,0x286ab13a,0xb18c3000,0x2e492c54,0xb0008000,0xb00031a8,0x30008000,0x3000b1a8,0x2e498000,0x318cb13a,0x286ab000,0xb0b42c54,
0xac548000,0xb13a3000,0xb13a31a8,0xac543000,0x286a8000,0x2e49ac54,0x30b4b000,0x318cb13a,0xb1a831a8,0xb1a831a8,0xb1a831a8,0xb1a831a8,
0x318cb1a8,0x30b4b13a,0x2e49b000,0x286aac54,0xb13a31a8,0xac543000,0x2c540000,0x313ab000,0x30b4b1a8,0xa86aac54,0xb18c3000,0xae49313a,
0xb00031a8,0x30000000,0x3000b1a8,0xb0008000,0x2e49b1a8,0xb18c2c54,0x286a3000,0x30b4b13a,0xac5431a8,0x313ab000,0xb13a8000,0x2c543000,
0x286ab1a8,0xae49313a,0x30b4b000,0xb18c2c54,0x80008000,0x80008000,0x80008000,0x80008000,0xa86a8000,0xae492c54,0xb0b43000,0xb18c313a,
0x2c548000,0x313ab000,0x313ab1a8,0x2c54b000,0xae498000,0xb18c313a,0xa86a3000,0x30b4ac54,0x30008000,0x3000b1a8,0xb0008000,0xb00031a8,
0xb0b48000,0xa86a313a,0x318cb000,0xae49ac54,0x313a8000,0xac54b000,0xac5431a8,0x313ab000,0xb18c8000,0x30b42c54,0xae49b000,0x286a313a,
0x800031a8,0xb1a8,0x800031a8,0xb1a8,0xa86ab1a8,0x2e49313a,0xb0b4b000,0x318c2c54,0x2c5431a8,0xb13ab000,0x313a0000,0xac543000,
0xae49b1a8,0x318c2c54,0xa86a3000,0xb0b4b13a,0x300031a8,0xb0008000,0xb000b1a8,0x30000000,0xb0b4b1a8,0x286aac54,0x318c3000,0x2e49313a,
0x313a31a8,0x2c543000,0xac548000,0xb13ab000,0xb18cb1a8,0xb0b4b13a,0xae49b000,0xa86aac54,0x31a88000,0xb1a88000,0x31a88000,0xb1a88000,
0xb18c8000,0x30b4ac54,0xae493000,0x286ab13a,0x313a8000,0xac543000,0xac54b1a8,0x313a3000,0xb0b48000,0xa86ab13a,0x318c3000,0xae492c54,
0x30008000,0x300031a8,0xb0008000,0xb000b1a8,0xae498000,0xb18cb13a,0xa86ab000,0x30b42c54,0x2c548000,0x313a3000,0x313a31a8,0x2c543000,
0xa86a8000,0xae49ac54,0xb0b4b000,0xb18cb13a,0x0,0x0,0x0,0x0,0xa86a0000,0xae49ac54,0xb0b4b000,0xb18cb13a,
0x2c540000,0x313a3000,0x313a31a8,0x2c543000,0xae490000,0xb18cb13a,0xa86ab000,0x30b42c54,0x30000000,0x300031a8,0xb0000000,0xb000b1a8,
0xb0b40000,0xa86ab13a,0x318c3000,0xae492c54,0x313a0000,0xac543000,0xac54b1a8,0x313a3000,0xb18c0000,0x30b4ac54,0xae493000,0x286ab13a,
0x31a831a8,0x31a831a8,0x31a831a8,0x31a831a8,0xb18cb1a8,0xb0b4b13a,0xae49b000,0xa86aac54,0x313a31a8,0x2c543000,0xac540000,0xb13ab000,
0xb0b4b1a8,0x286aac54,0x318c3000,0x2e49313a,0x300031a8,0xb0000000,0xb000b1a8,0x30008000,0xae49b1a8,0x318c2c54,0xa86a3000,0xb0b4b13a,
0x2c5431a8,0xb13ab000,0x313a8000,0xac543000,0xa86ab1a8,0x2e49313a,0xb0b4b000,0x318c2c54,0x31a80000,0xb1a80000,0x31a80000,0xb1a80000,
0xb18c0000,0x30b42c54,0xae49b000,0x286a313a,0x313a0000,0xac54b000,0xac5431a8,0x313ab000,0xb0b40000,0xa86a313a,0x318cb000,0xae49ac54,
0x30000000,0x3000b1a8,0xb0000000,0xb00031a8,0xae490000,0xb18c313a,0xa86a3000,0x30b4ac54,0x2c540000,0x313ab000,0x313ab1a8,0x2c54b000,
0xa86a0000,0xae492c54,0xb0b43000,0xb18c313a,0x31a8,0x8000b1a8,0x31a8,0x8000b1a8,0x286ab1a8,0xae49313a,0x30b4b000,0xb18c2c54,
0xac5431a8,0x313ab000,0xb13a0000,0x2c543000,0x2e49b1a8,0xb18c2c54,0x286a3000,0x30b4b13a,0xb00031a8,0x30008000,0x3000b1a8,0xb0000000,
0x30b4b1a8,0xa86aac54,0xb18c3000,0xae49313a,0xb13a31a8,0xac543000,0x2c548000,0x313ab000,0x318cb1a8,0x30b4b13a,0x2e49b000,0x286aac54,
0x0,0x0,0x0,0x0,0x286a0000,0x2e49ac54,0x30b4b000,0x318cb13a,0xac540000,0xb13a3000,0xb13a31a8,0xac543000,
0x2e490000,0x318cb13a,0x286ab000,0xb0b42c54,0xb0000000,0xb00031a8,0x30000000,0x3000b1a8,0x30b40000,0x286ab13a,0xb18c3000,0x2e492c54,
0xb13a0000,0x2c543000,0x2c54b1a8,0xb13a3000,0x318c0000,0xb0b4ac54,0x2e493000,0xa86ab13a,0xb1a831a8,0xb1a831a8,0xb1a831a8,0xb1a831a8,
0x318cb1a8,0x30b4b13a,0x2e49b000,0x286aac54,0xb13a31a8,0xac543000,0x2c540000,0x313ab000,0x30b4b1a8,0xa86aac54,0xb18c3000,0xae49313a,
0xb00031a8,0x30000000,0x3000b1a8,0xb0008000,0x2e49b1a8,0xb18c2c54,0x286a3000,0x30b4b13a,0xac5431a8,0x313ab000,0xb13a8000,0x2c543000,
0x286ab1a8,0xae49313a,0x30b4b000,0xb18c2c54,0xb1a80000,0x31a80000,0xb1a80000,0x31a80000,0x318c0000,0xb0b42c54,0x2e49b000,0xa86a313a,
0xb13a0000,0x2c54b000,0x2c5431a8,0xb13ab000,0x30b40000,0x286a313a,0xb18cb000,0x2e49ac54,0xb0000000,0xb000b1a8,0x30000000,0x300031a8,
0x2e490000,0x318c313a,0x286a3000,0xb0b4ac54,0xac540000,0xb13ab000,0xb13ab1a8,0xac54b000,0x286a0000,0x2e492c54,0x30b43000,0x318c313a,
0x800031a8,0xb1a8,0x800031a8,0xb1a8,0xa86ab1a8,0x2e49313a,0xb0b4b000,0x318c2c54,0x2c5431a8,0xb13ab000,0x313a0000,0xac543000,
0xae49b1a8,0x318c2c54,0xa86a3000,0xb0b4b13a,0x300031a8,0xb0008000,0xb000b1a8,0x30000000,0xb0b4b1a8,0x286aac54,0x318c3000,0x2e49313a,
0x313a31a8,0x2c543000,0xac548000,0xb13ab000,0xb18cb1a8,0xb0b4b13a,0xae49b000,0xa86aac54,0x31a831a8,0x31a831a8,0x31a831a8,0x31a831a8,
0x286a8000,0x2e492c54,0x30b43000,0x318c313a,0xb13ab1a8,0xac54b000,0x2c548000,0x313a3000,0xae490000,0xb18cb13a,0xa86ab000,0x30b42c54,
0x300031a8,0xb0000000,0xb000b1a8,0x30008000,0x30b48000,0x286a313a,0xb18cb000,0x2e49ac54,0xac54b1a8,0x313a3000,0xb13a0000,0x2c54b000,
0xb18c0000,0x30b4ac54,0xae493000,0x286ab13a,0x80008000,0x80008000,0x80008000,0x80008000,0x318c31a8,0x30b4313a,0x2e493000,0x286a2c54,
0x2c548000,0x313a3000,0x313a31a8,0x2c543000,0xb0b4b1a8,0x286aac54,0x318c3000,0x2e49313a,0xb0008000,0xb000b1a8,0x30008000,0x300031a8,
0x2e4931a8,0xb18cac54,0x286ab000,0x30b4313a,0x313a8000,0xac543000,0xac54b1a8,0x313a3000,0xa86ab1a8,0x2e49313a,0xb0b4b000,0x318c2c54,
0x31a8,0x8000b1a8,0x31a8,0x8000b1a8,0x318c8000,0xb0b4ac54,0x2e493000,0xa86ab13a,0x2c54b1a8,0xb13a3000,0x313a8000,0xac54b000,
0xb0b40000,0xa86a313a,0x318cb000,0xae49ac54,0xb00031a8,0x30008000,0x3000b1a8,0xb0000000,0x2e498000,0x318cb13a,0x286ab000,0xb0b42c54,
0x313ab1a8,0x2c54b000,0xac540000,0xb13a3000,0xa86a0000,0xae492c54,0xb0b43000,0xb18c313a,0xb1a88000,0x31a88000,0xb1a88000,0x31a88000,
0xa86a31a8,0x2e49b13a,0xb0b43000,0x318cac54,0x313a8000,0xac54b000,0xac5431a8,0x313ab000,0x2e49b1a8,0xb18c2c54,0x286a3000,0x30b4b13a,
0xb0008000,0xb00031a8,0x30008000,0x3000b1a8,0xb0b431a8,0x286a2c54,0x318cb000,0x2e49b13a,0x2c548000,0x313ab000,0x313ab1a8,0x2c54b000,
0x318cb1a8,0x30b4b13a,0x2e49b000,0x286aac54,0xb1a831a8,0xb1a831a8,0xb1a831a8,0xb1a831a8,0xa86a8000,0xae492c54,0xb0b43000,0xb18c313a,
0x313ab1a8,0x2c54b000,0xac548000,0xb13a3000,0x2e490000,0x318cb13a,0x286ab000,0xb0b42c54,0xb00031a8,0x30000000,0x3000b1a8,0xb0008000,
0xb0b48000,0xa86a313a,0x318cb000,0xae49ac54,0x2c54b1a8,0xb13a3000,0x313a0000,0xac54b000,0x318c0000,0xb0b4ac54,0x2e493000,0xa86ab13a,
0x80008000,0x80008000,0x80008000,0x80008000,0xb18c31a8,0xb0b4313a,0xae493000,0xa86a2c54,0xac548000,0xb13a3000,0xb13a31a8,0xac543000,
0x30b4b1a8,0xa86aac54,0xb18c3000,0xae49313a,0x30008000,0x3000b1a8,0xb0008000,0xb00031a8,0xae4931a8,0x318cac54,0xa86ab000,0xb0b4313a,
0xb13a8000,0x2c543000,0x2c54b1a8,0xb13a3000,0x286ab1a8,0xae49313a,0x30b4b000,0xb18c2c54,0x800031a8,0xb1a8,0x800031a8,0xb1a8,
0xb18c8000,0x30b4ac54,0xae493000,0x286ab13a,0xac54b1a8,0x313a3000,0xb13a8000,0x2c54b000,0x30b40000,0x286a313a,0xb18cb000,0x2e49ac54,
0x300031a8,0xb0008000,0xb000b1a8,0x30000000,0xae498000,0xb18cb13a,0xa86ab000,0x30b42c54,0xb13ab1a8,0xac54b000,0x2c540000,0x313a3000,
0x286a0000,0x2e492c54,0x30b43000,0x318c313a,0x31a88000,0xb1a88000,0x31a88000,0xb1a88000,0x286a31a8,0xae49b13a,0x30b43000,0xb18cac54,
0xb13a8000,0x2c54b000,0x2c5431a8,0xb13ab000,0xae49b1a8,0x318c2c54,0xa86a3000,0xb0b4b13a,0x30008000,0x300031a8,0xb0008000,0xb000b1a8,
0x30b431a8,0xa86a2c54,0xb18cb000,0xae49b13a,0xac548000,0xb13ab000,0xb13ab1a8,0xac54b000,0xb18cb1a8,0xb0b4b13a,0xae49b000,0xa86aac54,
0x0,0x0,0x0,0x0,0xb18cb1a8,0xb0b4b13a,0xae49b000,0xa86aac54,0xac540000,0xb13ab000,0xb13ab1a8,0xac54b000,
0x30b431a8,0xa86a2c54,0xb18cb000,0xae49b13a,0x30000000,0x300031a8,0xb0000000,0xb000b1a8,0xae49b1a8,0x318c2c54,0xa86a3000,0xb0b4b13a,
0xb13a0000,0x2c54b000,0x2c5431a8,0xb13ab000,0x286a31a8,0xae49b13a,0x30b43000,0xb18cac54,0x31a831a8,0x31a831a8,0x31a831a8,0x31a831a8,
0x286a8000,0x2e492c54,0x30b43000,0x318c313a,0xb13ab1a8,0xac54b000,0x2c548000,0x313a3000,0xae490000,0xb18cb13a,0xa86ab000,0x30b42c54,
0x300031a8,0xb0000000,0xb000b1a8,0x30008000,0x30b48000,0x286a313a,0xb18cb000,0x2e49ac54,0xac54b1a8,0x313a3000,0xb13a0000,0x2c54b000,
0xb18c0000,0x30b4ac54,0xae493000,0x286ab13a,0x31a80000,0xb1a80000,0x31a80000,0xb1a80000,0x286ab1a8,0xae49313a,0x30b4b000,0xb18c2c54,
0xb13a0000,0x2c543000,0x2c54b1a8,0xb13a3000,0xae4931a8,0x318cac54,0xa86ab000,0xb0b4313a,0x30000000,0x3000b1a8,0xb0000000,0xb00031a8,
0x30b4b1a8,0xa86aac54,0xb18c3000,0xae49313a,0xac540000,0xb13a3000,0xb13a31a8,0xac543000,0xb18c31a8,0xb0b4313a,0xae493000,0xa86a2c54,
0x31a8,0x8000b1a8,0x31a8,0x8000b1a8,0x318c8000,0xb0b4ac54,0x2e493000,0xa86ab13a,0x2c54b1a8,0xb13a3000,0x313a8000,0xac54b000,
0xb0b40000,0xa86a313a,0x318cb000,0xae49ac54,0xb00031a8,0x30008000,0x3000b1a8,0xb0000000,0x2e498000,0x318cb13a,0x286ab000,0xb0b42c54,
0x313ab1a8,0x2c54b000,0xac540000,0xb13a3000,0xa86a0000,0xae492c54,0xb0b43000,0xb18c313a,0x0,0x0,0x0,0x0,
0x318cb1a8,0x30b4b13a,0x2e49b000,0x286aac54,0x2c540000,0x313ab000,0x313ab1a8,0x2c54b000,0xb0b431a8,0x286a2c54,0x318cb000,0x2e49b13a,
0xb0000000,0xb00031a8,0x30000000,0x3000b1a8,0x2e49b1a8,0xb18c2c54,0x286a3000,0x30b4b13a,0x313a0000,0xac54b000,0xac5431a8,0x313ab000,
0xa86a31a8,0x2e49b13a,0xb0b43000,0x318cac54,0xb1a831a8,0xb1a831a8,0xb1a831a8,0xb1a831a8,0xa86a8000,0xae492c54,0xb0b43000,0xb18c313a,
0x313ab1a8,0x2c54b000,0xac548000,0xb13a3000,0x2e490000,0x318cb13a,0x286ab000,0xb0b42c54,0xb00031a8,0x30000000,0x3000b1a8,0xb0008000,
0xb0b48000,0xa86a313a,0x318cb000,0xae49ac54,0x2c54b1a8,0xb13a3000,0x313a0000,0xac54b000,0x318c0000,0xb0b4ac54,0x2e493000,0xa86ab13a,
0xb1a80000,0x31a80000,0xb1a80000,0x31a80000,0xa86ab1a8,0x2e49313a,0xb0b4b000,0x318c2c54,0x313a0000,0xac543000,0xac54b1a8,0x313a3000,
0x2e4931a8,0xb18cac54,0x286ab000,0x30b4313a,0xb0000000,0xb000b1a8,0x30000000,0x300031a8,0xb0b4b1a8,0x286aac54,0x318c3000,0x2e49313a,
0x2c540000,0x313a3000,0x313a31a8,0x2c543000,0x318c31a8,0x30b4313a,0x2e493000,0x286a2c54,0x800031a8,0xb1a8,0x800031a8,0xb1a8,
0xb18c8000,0x30b4ac54,0xae493000,0x286ab13a,0xac54b1a8,0x313a3000,0xb13a8000,0x2c54b000,0x30b40000,0x286a313a,0xb18cb000,0x2e49ac54,
0x300031a8,0xb0008000,0xb000b1a8,0x30000000,0xae498000,0xb18cb13a,0xa86ab000,0x30b42c54,0xb13ab1a8,0xac54b000,0x2c540000,0x313a3000,
0x286a0000,0x2e492c54,0x30b43000,0x318c313a,0x2d0f290f,0x2d0f2d0f,0x2d0f2d0f,0x2d0f2d0f,0x2d0f2d0f,0x2d0f2d0f,0x2d0f2d0f,0x2d0f2d0f,
0x2d0f2d0f,0x2d0f2d0f,0x2d0f2d0f,0x2d0f2d0f,0x2d0f2d0f,0x2d0f2d0f,0x2d0f2d0f,0x2d0f2d0f,0x290f,0x0,0x0,0x0,
0x0,0x0,0x0,0x0,0x0,0x0,0x0,0x0,0x0,0x0,0x0,0x0,
0x2a6b2b28,0x28c5299f,0x25e027bf,0x1fef23e6,0x2d09290f,0x2cd72cf6,0x2c762cad,0x2bd32c35,0xabd3ab28,0xac76ac35,0xacd7acad,0xad09acf6,
0x9fef0000,0xa5e0a3e6,0xa8c5a7bf,0xaa6ba99f,0x2bd32b28,0x2c762c35,0x2cd72cad,0x2d092cf6,0x1fefa90f,0x25e023e6,0x28c527bf,0x2a6b299f,
0x2a6b2b28,0x28c5299f,0x25e027bf,0x1fef23e6,0x2d092d0f,0x2cd72cf6,0x2c762cad,0x2bd32c35,0xacf6ad0f,0xac35acad,0xa99fab28,0xa3e6a7bf,
0x23e68000,0x299f27bf,0x2c352b28,0x2cf62cad,0x2cf6290f,0x2c352cad,0x299f2b28,0x23e627bf,0xa3e60000,0xa99fa7bf,0xac35ab28,0xacf6acad,
0xa3e60000,0xa99fa7bf,0xac35ab28,0xacf6acad,0xacf6ad0f,0xac35acad,0xa99fab28,0xa3e6a7bf,0x23e6290f,0x299f27bf,0x2c352b28,0x2cf62cad,
0x2cf62d0f,0x2c352cad,0x299f2b28,0x23e627bf,0x28c52b28,0x9fef23e6,0xaa6ba7bf,0xacd7ac35,0x25e08000,0x2bd3299f,0x2d092cad,0x2c762cf6,
0xac76ab28,0xad09acf6,0xabd3acad,0xa5e0a99f,0x2cd7290f,0x2a6b2c35,0x1fef27bf,0xa8c5a3e6,0x2c762b28,0x2d092cf6,0x2bd32cad,0x25e0299f,
0xacd7ad0f,0xaa6bac35,0x9fefa7bf,0x28c523e6,0x28c52b28,0x9fef23e6,0xaa6ba7bf,0xacd7ac35,0x25e0a90f,0x2bd3299f,0x2d092cad,0x2c762cf6,
0x27bf290f,0x2cad2b28,0x2cad2d0f,0x27bf2b28,0xa7bf0000,0xacadab28,0xacadad0f,0xa7bfab28,0x27bf0000,0x2cad2b28,0x2cad2d0f,0x27bf2b28,
0xa7bf0000,0xacadab28,0xacadad0f,0xa7bfab28,0x2cad290f,0x27bf2b28,0xa7bf0000,0xacadab28,0xacadad0f,0xa7bfab28,0x27bf8000,0x2cad2b28,
0x2cad2d0f,0x27bf2b28,0xa7bf0000,0xacadab28,0xacadad0f,0xa7bfab28,0x27bf8000,0x2cad2b28,0xacd7ab28,0xabd3acf6,0x1fefa7bf,0x2c76299f,
0x28c5a90f,0x2d092c35,0x2a6b2cad,0xa5e023e6,0xa5e0ab28,0x2a6b23e6,0x2d092cad,0x28c52c35,0x2c762d0f,0x1fef299f,0xabd3a7bf,0xacd7acf6,
0xa5e0ab28,0x2a6b23e6,0x2d092cad,0x28c52c35,0x2c76290f,0x1fef299f,0xabd3a7bf,0xacd7acf6,0x2cd72b28,0x2bd32cf6,0x9fef27bf,0xac76a99f,
0xa8c50000,0xad09ac35,0xaa6bacad,0x25e0a3e6,0xa99f0000,0xacf6acad,0xa3e6ab28,0x2c3527bf,0x2c352d0f,0xa3e627bf,0xacf6ab28,0xa99facad,
0x299f290f,0x2cf62cad,0x23e62b28,0xac35a7bf,0xac35ad0f,0x23e6a7bf,0x2cf62b28,0x299f2cad,0xac35ad0f,0x23e6a7bf,0x2cf62b28,0x299f2cad,
0xa99f0000,0xacf6acad,0xa3e6ab28,0x2c3527bf,0x2c35290f,0xa3e627bf,0xacf6ab28,0xa99facad,0x299f8000,0x2cf62cad,0x23e62b28,0xac35a7bf,
0xad09ab28,0xa5e0ac35,0x2c7627bf,0x2a6b2cf6,0xabd3ad0f,0x28c5a3e6,0x2cd72cad,0x9fef299f,0x9fefab28,0x2cd7299f,0x28c52cad,0xabd3a3e6,
0x2a6ba90f,0x2c762cf6,0xa5e027bf,0xad09ac35,0x9fefab28,0x2cd7299f,0x28c52cad,0xabd3a3e6,0x2a6b8000,0x2c762cf6,0xa5e027bf,0xad09ac35,
0x2d092b28,0x25e02c35,0xac76a7bf,0xaa6bacf6,0x2bd3290f,0xa8c523e6,0xacd7acad,0x1fefa99f,0x2b28290f,0xab280000,0xab28ad0f,0x2b288000,
0x2b282d0f,0xab280000,0xab28ad0f,0x2b288000,0x2b282d0f,0xab280000,0xab28ad0f,0x2b288000,0x2b282d0f,0xab280000,0xab28ad0f,0x2b288000,
0x2b28290f,0x2b282d0f,0xab280000,0xab28ad0f,0x2b280000,0x2b282d0f,0xab280000,0xab28ad0f,0x2b280000,0x2b282d0f,0xab280000,0xab28ad0f,
0x2b280000,0x2b282d0f,0xab280000,0xab28ad0f,0x9fef2b28,0xacd7ac35,0x28c5a7bf,0x2bd32cf6,0x2a6b290f,0xac76a3e6,0xa5e0acad,0x2d09299f,
0xad09ab28,0x25e0a99f,0x2c762cad,0xaa6b23e6,0xabd30000,0xa8c5acf6,0x2cd727bf,0x1fef2c35,0x2d092b28,0xa5e0299f,0xac76acad,0x2a6ba3e6,
0x2bd3a90f,0x28c52cf6,0xacd7a7bf,0x9fefac35,0x9fef2b28,0xacd7ac35,0x28c5a7bf,0x2bd32cf6,0x2a6b2d0f,0xac76a3e6,0xa5e0acad,0x2d09299f,
0xa99fad0f,0x2cf627bf,0xa3e62b28,0xac35acad,0x2c358000,0x23e62cad,0xacf6ab28,0x299fa7bf,0x299f290f,0xacf6a7bf,0x23e6ab28,0x2c352cad,
0xac350000,0xa3e6acad,0x2cf62b28,0xa99f27bf,0xac350000,0xa3e6acad,0x2cf62b28,0xa99f27bf,0xa99fad0f,0x2cf627bf,0xa3e62b28,0xac35acad,
0x2c35290f,0x23e62cad,0xacf6ab28,0x299fa7bf,0x299f2d0f,0xacf6a7bf,0x23e6ab28,0x2c352cad,0xa5e02b28,0xaa6bacf6,0x2d0927bf,0xa8c5299f,
0x2c768000,0x9fef2c35,0xabd3acad,0x2cd723e6,0xacd7ab28,0x2bd3a3e6,0x1fef2cad,0xac76ac35,0x28c5290f,0xad09a99f,0x2a6ba7bf,0x25e02cf6,
0x2cd72b28,0xabd323e6,0x9fefacad,0x2c762c35,0xa8c5ad0f,0x2d09299f,0xaa6b27bf,0xa5e0acf6,0xa5e02b28,0xaa6bacf6,0x2d0927bf,0xa8c5299f,
0x2c76a90f,0x9fef2c35,0xabd3acad,0x2cd723e6,0x2cad290f,0xa7bf2b28,0xa7bfad0f,0x2cad2b28,0xacad0000,0x27bfab28,0x27bf2d0f,0xacadab28,
0x2cad0000,0xa7bf2b28,0xa7bfad0f,0x2cad2b28,0xacad0000,0x27bfab28,0x27bf2d0f,0xacadab28,0x27bf290f,0xacadab28,0x2cad8000,0xa7bf2b28,
0xa7bfad0f,0x2cad2b28,0xacad0000,0x27bfab28,0x27bf2d0f,0xacadab28,0x2cad8000,0xa7bf2b28,0xa7bfad0f,0x2cad2b28,0xacad0000,0x27bfab28,
0xac76ab28,0x2d0923e6,0xabd327bf,0x25e0ac35,0x2cd7a90f,0xaa6b299f,0x1fefacad,0x28c52cf6,0x28c5ab28,0x1fef2cf6,0xaa6bacad,0x2cd7299f,
0x25e02d0f,0xabd3ac35,0x2d0927bf,0xac7623e6,0x28c5ab28,0x1fef2cf6,0xaa6bacad,0x2cd7299f,0x25e0290f,0xabd3ac35,0x2d0927bf,0xac7623e6,
0x2c762b28,0xad09a3e6,0x2bd3a7bf,0xa5e02c35,0xacd70000,0x2a6ba99f,0x9fef2cad,0xa8c5acf6,0xacf60000,0x2c35a7bf,0xa99f2b28,0x23e6acad,
0x23e62d0f,0xa99facad,0x2c352b28,0xacf6a7bf,0x2cf6290f,0xac3527bf,0x299fab28,0xa3e62cad,0xa3e6ad0f,0x299f2cad,0xac35ab28,0x2cf627bf,
0xa3e6ad0f,0x299f2cad,0xac35ab28,0x2cf627bf,0xacf60000,0x2c35a7bf,0xa99f2b28,0x23e6acad,0x23e6290f,0xa99facad,0x2c352b28,0xacf6a7bf,
0x2cf68000,0xac3527bf,0x299fab28,0xa3e62cad,0xabd3ab28,0x2c76299f,0xacd7a7bf,0x2d0923e6,0x9fefad0f,0x25e02cf6,0xa8c5acad,0x2a6b2c35,
0x2a6bab28,0xa8c52c35,0x25e0acad,0x9fef2cf6,0x2d09a90f,0xacd723e6,0x2c76a7bf,0xabd3299f,0x2a6bab28,0xa8c52c35,0x25e0acad,0x9fef2cf6,
0x2d098000,0xacd723e6,0x2c76a7bf,0xabd3299f,0x2bd32b28,0xac76a99f,0x2cd727bf,0xad09a3e6,0x1fef290f,0xa5e0acf6,0x28c52cad,0xaa6bac35,
0x290f,0x8000ad0f,0x2d0f,0x8000ad0f,0x2d0f,0x8000ad0f,0x2d0f,0x8000ad0f,0x2d0f,0x8000ad0f,0x2d0f,0x8000ad0f,
0x2d0f,0x8000ad0f,0x2d0f,0x8000ad0f,0x2d0f290f,0xad0f0000,0x2d0f0000,0xad0f0000,0x2d0f0000,0xad0f0000,0x2d0f0000,0xad0f0000,
0x2d0f0000,0xad0f0000,0x2d0f0000,0xad0f0000,0x2d0f0000,0xad0f0000,0x2d0f0000,0xad0f0000,0xabd32b28,0x2c76a99f,0xacd727bf,0x2d09a3e6,
0x9fef290f,0x25e0acf6,0xa8c52cad,0x2a6bac35,0xaa6bab28,0x28c52c35,0xa5e0acad,0x1fef2cf6,0xad090000,0x2cd723e6,0xac76a7bf,0x2bd3299f,
0x2a6b2b28,0xa8c5ac35,0x25e02cad,0x9fefacf6,0x2d09a90f,0xacd7a3e6,0x2c7627bf,0xabd3a99f,0xabd32b28,0x2c76a99f,0xacd727bf,0x2d09a3e6,
0x9fef2d0f,0x25e0acf6,0xa8c52cad,0x2a6bac35,0x23e6ad0f,0xa99f2cad,0x2c35ab28,0xacf627bf,0x2cf68000,0xac35a7bf,0x299f2b28,0xa3e6acad,
0xa3e6290f,0x299facad,0xac352b28,0x2cf6a7bf,0xacf60000,0x2c3527bf,0xa99fab28,0x23e62cad,0xacf60000,0x2c3527bf,0xa99fab28,0x23e62cad,
0x23e6ad0f,0xa99f2cad,0x2c35ab28,0xacf627bf,0x2cf6290f,0xac35a7bf,0x299f2b28,0xa3e6acad,0xa3e62d0f,0x299facad,0xac352b28,0x2cf6a7bf,
0xac762b28,0x2d09a3e6,0xabd3a7bf,0x25e02c35,0x2cd78000,0xaa6ba99f,0x1fef2cad,0x28c5acf6,0xa8c5ab28,0x9fef2cf6,0x2a6bacad,0xacd7299f,
0xa5e0290f,0x2bd3ac35,0xad0927bf,0x2c7623e6,0x28c52b28,0x1fefacf6,0xaa6b2cad,0x2cd7a99f,0x25e0ad0f,0xabd32c35,0x2d09a7bf,0xac76a3e6,
0xac762b28,0x2d09a3e6,0xabd3a7bf,0x25e02c35,0x2cd7a90f,0xaa6ba99f,0x1fef2cad,0x28c5acf6,0x2cad290f,0xa7bfab28,0xa7bf2d0f,0x2cadab28,
0xacad0000,0x27bf2b28,0x27bfad0f,0xacad2b28,0x2cad0000,0xa7bfab28,0xa7bf2d0f,0x2cadab28,0xacad0000,0x27bf2b28,0x27bfad0f,0xacad2b28,
0xa7bf290f,0x2cadab28,0xacad0000,0x27bf2b28,0x27bfad0f,0xacad2b28,0x2cad8000,0xa7bfab28,0xa7bf2d0f,0x2cadab28,0xacad0000,0x27bf2b28,
0x27bfad0f,0xacad2b28,0x2cad8000,0xa7bfab28,0xa5e0ab28,0xaa6b2cf6,0x2d09a7bf,0xa8c5a99f,0x2c76a90f,0x9fefac35,0xabd32cad,0x2cd7a3e6,
0x2cd7ab28,0xabd3a3e6,0x9fef2cad,0x2c76ac35,0xa8c52d0f,0x2d09a99f,0xaa6ba7bf,0xa5e02cf6,0x2cd7ab28,0xabd3a3e6,0x9fef2cad,0x2c76ac35,
0xa8c5290f,0x2d09a99f,0xaa6ba7bf,0xa5e02cf6,0x25e02b28,0x2a6bacf6,0xad0927bf,0x28c5299f,0xac760000,0x1fef2c35,0x2bd3acad,0xacd723e6,
0xac350000,0xa3e62cad,0x2cf6ab28,0xa99fa7bf,0xa99f2d0f,0x2cf6a7bf,0xa3e6ab28,0xac352cad,0x2c35290f,0x23e6acad,0xacf62b28,0x299f27bf,
0x299fad0f,0xacf627bf,0x23e62b28,0x2c35acad,0x299fad0f,0xacf627bf,0x23e62b28,0x2c35acad,0xac350000,0xa3e62cad,0x2cf6ab28,0xa99fa7bf,
0xa99f290f,0x2cf6a7bf,0xa3e6ab28,0xac352cad,0x2c358000,0x23e6acad,0xacf62b28,0x299f27bf,0x9fefab28,0xacd72c35,0x28c527bf,0x2bd3acf6,
0x2a6bad0f,0xac7623e6,0xa5e02cad,0x2d09a99f,0x2d09ab28,0xa5e0a99f,0xac762cad,0x2a6b23e6,0x2bd3a90f,0x28c5acf6,0xacd727bf,0x9fef2c35,
0x2d09ab28,0xa5e0a99f,0xac762cad,0x2a6b23e6,0x2bd38000,0x28c5acf6,0xacd727bf,0x9fef2c35,0x1fef2b28,0x2cd7ac35,0xa8c5a7bf,0xabd32cf6,
0xaa6b290f,0x2c76a3e6,0x25e0acad,0xad09299f,0xab28290f,0x2b288000,0x2b28ad0f,0xab280000,0xab282d0f,0x2b288000,0x2b28ad0f,0xab280000,
0xab282d0f,0x2b288000,0x2b28ad0f,0xab280000,0xab282d0f,0x2b288000,0x2b28ad0f,0xab280000,0x2b28290f,0x2b28ad0f,0xab280000,0xab282d0f,
0x2b280000,0x2b28ad0f,0xab280000,0xab282d0f,0x2b280000,0x2b28ad0f,0xab280000,0xab282d0f,0x2b280000,0x2b28ad0f,0xab280000,0xab282d0f,
0xad092b28,0xa5e02c35,0x2c76a7bf,0x2a6bacf6,0xabd3290f,0x28c523e6,0x2cd7acad,0x9fefa99f,0x1fefab28,0xacd7299f,0xa8c52cad,0x2bd3a3e6,
0xaa6b0000,0xac762cf6,0x25e027bf,0x2d09ac35,0x9fef2b28,0x2cd7a99f,0x28c5acad,0xabd323e6,0x2a6ba90f,0x2c76acf6,0xa5e0a7bf,0xad092c35,
0xad092b28,0xa5e02c35,0x2c76a7bf,0x2a6bacf6,0xabd32d0f,0x28c523e6,0x2cd7acad,0x9fefa99f,0x2c35ad0f,0xa3e6a7bf,0xacf62b28,0xa99f2cad,
0x299f8000,0x2cf6acad,0x23e6ab28,0xac3527bf,0xac35290f,0x23e627bf,0x2cf6ab28,0x299facad,0xa99f0000,0xacf62cad,0xa3e62b28,0x2c35a7bf,
0xa99f0000,0xacf62cad,0xa3e62b28,0x2c35a7bf,0x2c35ad0f,0xa3e6a7bf,0xacf62b28,0xa99f2cad,0x299f290f,0x2cf6acad,0x23e6ab28,0xac3527bf,
0xac352d0f,0x23e627bf,0x2cf6ab28,0x299facad,0xacd72b28,0xabd32cf6,0x1fef27bf,0x2c76a99f,0x28c58000,0x2d09ac35,0x2a6bacad,0xa5e0a3e6,
0x25e0ab28,0xaa6b23e6,0xad092cad,0xa8c52c35,0xac76290f,0x9fef299f,0x2bd3a7bf,0x2cd7acf6,0xa5e02b28,0x2a6ba3e6,0x2d09acad,0x28c5ac35,
0x2c76ad0f,0x1fefa99f,0xabd327bf,0xacd72cf6,0xacd72b28,0xabd32cf6,0x1fef27bf,0x2c76a99f,0x28c5a90f,0x2d09ac35,0x2a6bacad,0xa5e0a3e6,
0x27bf290f,0x2cadab28,0x2cadad0f,0x27bfab28,0xa7bf0000,0xacad2b28,0xacad2d0f,0xa7bf2b28,0x27bf0000,0x2cadab28,0x2cadad0f,0x27bfab28,
0xa7bf0000,0xacad2b28,0xacad2d0f,0xa7bf2b28,0xacad290f,0xa7bf2b28,0x27bf8000,0x2cadab28,0x2cadad0f,0x27bfab28,0xa7bf0000,0xacad2b28,
0xacad2d0f,0xa7bf2b28,0x27bf8000,0x2cadab28,0x2cadad0f,0x27bfab28,0xa7bf0000,0xacad2b28,0x28c5ab28,0x9fefa3e6,0xaa6b27bf,0xacd72c35,
0x25e0a90f,0x2bd3a99f,0x2d09acad,0x2c76acf6,0x2c76ab28,0x2d09acf6,0x2bd3acad,0x25e0a99f,0xacd72d0f,0xaa6b2c35,0x9fef27bf,0x28c5a3e6,
0x2c76ab28,0x2d09acf6,0x2bd3acad,0x25e0a99f,0xacd7290f,0xaa6b2c35,0x9fef27bf,0x28c5a3e6,0xa8c52b28,0x1fef23e6,0x2a6ba7bf,0x2cd7ac35,
0xa5e00000,0xabd3299f,0xad092cad,0xac762cf6,0xa3e60000,0xa99f27bf,0xac352b28,0xacf62cad,0xacf62d0f,0xac352cad,0xa99f2b28,0xa3e627bf,
0x23e6290f,0x299fa7bf,0x2c35ab28,0x2cf6acad,0x2cf6ad0f,0x2c35acad,0x299fab28,0x23e6a7bf,0x2cf6ad0f,0x2c35acad,0x299fab28,0x23e6a7bf,
0xa3e60000,0xa99f27bf,0xac352b28,0xacf62cad,0xacf6290f,0xac352cad,0xa99f2b28,0xa3e627bf,0x23e68000,0x299fa7bf,0x2c35ab28,0x2cf6acad,
0x2a6bab28,0x28c5a99f,0x25e0a7bf,0x1fefa3e6,0x2d09ad0f,0x2cd7acf6,0x2c76acad,0x2bd3ac35,0x2bd3ab28,0x2c76ac35,0x2cd7acad,0x2d09acf6,
0x1fefa90f,0x25e0a3e6,0x28c5a7bf,0x2a6ba99f,0x2bd3ab28,0x2c76ac35,0x2cd7acad,0x2d09acf6,0x1fef8000,0x25e0a3e6,0x28c5a7bf,0x2a6ba99f,
0xaa6b2b28,0xa8c5299f,0xa5e027bf,0x9fef23e6,0xad09290f,0xacd72cf6,0xac762cad,0xabd32c35,0xad0f290f,0xad0f2d0f,0xad0f2d0f,0xad0f2d0f,
0xad0f2d0f,0xad0f2d0f,0xad0f2d0f,0xad0f2d0f,0xad0f2d0f,0xad0f2d0f,0xad0f2d0f,0xad0f2d0f,0xad0f2d0f,0xad0f2d0f,0xad0f2d0f,0xad0f2d0f,
0x290f,0x0,0x0,0x0,0x0,0x0,0x0,0x0,0x0,0x0,0x0,0x0,
0x0,0x0,0x0,0x0,0xaa6b2b28,0xa8c5299f,0xa5e027bf,0x9fef23e6,0xad09290f,0xacd72cf6,0xac762cad,0xabd32c35,
0x2bd3ab28,0x2c76ac35,0x2cd7acad,0x2d09acf6,0x1fef0000,0x25e0a3e6,0x28c5a7bf,0x2a6ba99f,0xabd32b28,0xac762c35,0xacd72cad,0xad092cf6,
0x9fefa90f,0xa5e023e6,0xa8c527bf,0xaa6b299f,0xaa6b2b28,0xa8c5299f,0xa5e027bf,0x9fef23e6,0xad092d0f,0xacd72cf6,0xac762cad,0xabd32c35,
0x2cf6ad0f,0x2c35acad,0x299fab28,0x23e6a7bf,0xa3e68000,0xa99f27bf,0xac352b28,0xacf62cad,0xacf6290f,0xac352cad,0xa99f2b28,0xa3e627bf,
0x23e60000,0x299fa7bf,0x2c35ab28,0x2cf6acad,0x23e60000,0x299fa7bf,0x2c35ab28,0x2cf6acad,0x2cf6ad0f,0x2c35acad,0x299fab28,0x23e6a7bf,
0xa3e6290f,0xa99f27bf,0xac352b28,0xacf62cad,0xacf62d0f,0xac352cad,0xa99f2b28,0xa3e627bf,0xa8c52b28,0x1fef23e6,0x2a6ba7bf,0x2cd7ac35,
0xa5e08000,0xabd3299f,0xad092cad,0xac762cf6,0x2c76ab28,0x2d09acf6,0x2bd3acad,0x25e0a99f,0xacd7290f,0xaa6b2c35,0x9fef27bf,0x28c5a3e6,
0xac762b28,0xad092cf6,0xabd32cad,0xa5e0299f,0x2cd7ad0f,0x2a6bac35,0x1fefa7bf,0xa8c523e6,0xa8c52b28,0x1fef23e6,0x2a6ba7bf,0x2cd7ac35,
0xa5e0a90f,0xabd3299f,0xad092cad,0xac762cf6,0xa7bf290f,0xacad2b28,0xacad2d0f,0xa7bf2b28,0x27bf0000,0x2cadab28,0x2cadad0f,0x27bfab28,
0xa7bf0000,0xacad2b28,0xacad2d0f,0xa7bf2b28,0x27bf0000,0x2cadab28,0x2cadad0f,0x27bfab28,0xacad290f,0xa7bf2b28,0x27bf0000,0x2cadab28,
0x2cadad0f,0x27bfab28,0xa7bf8000,0xacad2b28,0xacad2d0f,0xa7bf2b28,0x27bf0000,0x2cadab28,0x2cadad0f,0x27bfab28,0xa7bf8000,0xacad2b28,
0x2cd7ab28,0x2bd3acf6,0x9fefa7bf,0xac76299f,0xa8c5a90f,0xad092c35,0xaa6b2cad,0x25e023e6,0x25e0ab28,0xaa6b23e6,0xad092cad,0xa8c52c35,
0xac762d0f,0x9fef299f,0x2bd3a7bf,0x2cd7acf6,0x25e0ab28,0xaa6b23e6,0xad092cad,0xa8c52c35,0xac76290f,0x9fef299f,0x2bd3a7bf,0x2cd7acf6,
0xacd72b28,0xabd32cf6,0x1fef27bf,0x2c76a99f,0x28c50000,0x2d09ac35,0x2a6bacad,0xa5e0a3e6,0x299f0000,0x2cf6acad,0x23e6ab28,0xac3527bf,
0xac352d0f,0x23e627bf,0x2cf6ab28,0x299facad,0xa99f290f,0xacf62cad,0xa3e62b28,0x2c35a7bf,0x2c35ad0f,0xa3e6a7bf,0xacf62b28,0xa99f2cad,
0x2c35ad0f,0xa3e6a7bf,0xacf62b28,0xa99f2cad,0x299f0000,0x2cf6acad,0x23e6ab28,0xac3527bf,0xac35290f,0x23e627bf,0x2cf6ab28,0x299facad,
0xa99f8000,0xacf62cad,0xa3e62b28,0x2c35a7bf,0x2d09ab28,0x25e0ac35,0xac7627bf,0xaa6b2cf6,0x2bd3ad0f,0xa8c5a3e6,0xacd72cad,0x1fef299f,
0x1fefab28,0xacd7299f,0xa8c52cad,0x2bd3a3e6,0xaa6ba90f,0xac762cf6,0x25e027bf,0x2d09ac35,0x1fefab28,0xacd7299f,0xa8c52cad,0x2bd3a3e6,
0xaa6b8000,0xac762cf6,0x25e027bf,0x2d09ac35,0xad092b28,0xa5e02c35,0x2c76a7bf,0x2a6bacf6,0xabd3290f,0x28c523e6,0x2cd7acad,0x9fefa99f,
0xab28290f,0x2b280000,0x2b28ad0f,0xab288000,0xab282d0f,0x2b280000,0x2b28ad0f,0xab288000,0xab282d0f,0x2b280000,0x2b28ad0f,0xab288000,
0xab282d0f,0x2b280000,0x2b28ad0f,0xab288000,0xab28290f,0xab282d0f,0x2b280000,0x2b28ad0f,0xab280000,0xab282d0f,0x2b280000,0x2b28ad0f,
0xab280000,0xab282d0f,0x2b280000,0x2b28ad0f,0xab280000,0xab282d0f,0x2b280000,0x2b28ad0f,0x1fef2b28,0x2cd7ac35,0xa8c5a7bf,0xabd32cf6,
0xaa6b290f,0x2c76a3e6,0x25e0acad,0xad09299f,0x2d09ab28,0xa5e0a99f,0xac762cad,0x2a6b23e6,0x2bd30000,0x28c5acf6,0xacd727bf,0x9fef2c35,
0xad092b28,0x25e0299f,0x2c76acad,0xaa6ba3e6,0xabd3a90f,0xa8c52cf6,0x2cd7a7bf,0x1fefac35,0x1fef2b28,0x2cd7ac35,0xa8c5a7bf,0xabd32cf6,
0xaa6b2d0f,0x2c76a3e6,0x25e0acad,0xad09299f,0x299fad0f,0xacf627bf,0x23e62b28,0x2c35acad,0xac358000,0xa3e62cad,0x2cf6ab28,0xa99fa7bf,
0xa99f290f,0x2cf6a7bf,0xa3e6ab28,0xac352cad,0x2c350000,0x23e6acad,0xacf62b28,0x299f27bf,0x2c350000,0x23e6acad,0xacf62b28,0x299f27bf,
0x299fad0f,0xacf627bf,0x23e62b28,0x2c35acad,0xac35290f,0xa3e62cad,0x2cf6ab28,0xa99fa7bf,0xa99f2d0f,0x2cf6a7bf,0xa3e6ab28,0xac352cad,
0x25e02b28,0x2a6bacf6,0xad0927bf,0x28c5299f,0xac768000,0x1fef2c35,0x2bd3acad,0xacd723e6,0x2cd7ab28,0xabd3a3e6,0x9fef2cad,0x2c76ac35,
0xa8c5290f,0x2d09a99f,0xaa6ba7bf,0xa5e02cf6,0xacd72b28,0x2bd323e6,0x1fefacad,0xac762c35,0x28c5ad0f,0xad09299f,0x2a6b27bf,0x25e0acf6,
0x25e02b28,0x2a6bacf6,0xad0927bf,0x28c5299f,0xac76a90f,0x1fef2c35,0x2bd3acad,0xacd723e6,0xacad290f,0x27bf2b28,0x27bfad0f,0xacad2b28,
0x2cad0000,0xa7bfab28,0xa7bf2d0f,0x2cadab28,0xacad0000,0x27bf2b28,0x27bfad0f,0xacad2b28,0x2cad0000,0xa7bfab28,0xa7bf2d0f,0x2cadab28,
0xa7bf290f,0x2cadab28,0xacad8000,0x27bf2b28,0x27bfad0f,0xacad2b28,0x2cad0000,0xa7bfab28,0xa7bf2d0f,0x2cadab28,0xacad8000,0x27bf2b28,
0x27bfad0f,0xacad2b28,0x2cad0000,0xa7bfab28,0x2c76ab28,0xad0923e6,0x2bd327bf,0xa5e0ac35,0xacd7a90f,0x2a6b299f,0x9fefacad,0xa8c52cf6,
0xa8c5ab28,0x9fef2cf6,0x2a6bacad,0xacd7299f,0xa5e02d0f,0x2bd3ac35,0xad0927bf,0x2c7623e6,0xa8c5ab28,0x9fef2cf6,0x2a6bacad,0xacd7299f,
0xa5e0290f,0x2bd3ac35,0xad0927bf,0x2c7623e6,0xac762b28,0x2d09a3e6,0xabd3a7bf,0x25e02c35,0x2cd70000,0xaa6ba99f,0x1fef2cad,0x28c5acf6,
0x2cf60000,0xac35a7bf,0x299f2b28,0xa3e6acad,0xa3e62d0f,0x299facad,0xac352b28,0x2cf6a7bf,0xacf6290f,0x2c3527bf,0xa99fab28,0x23e62cad,
0x23e6ad0f,0xa99f2cad,0x2c35ab28,0xacf627bf,0x23e6ad0f,0xa99f2cad,0x2c35ab28,0xacf627bf,0x2cf60000,0xac35a7bf,0x299f2b28,0xa3e6acad,
0xa3e6290f,0x299facad,0xac352b28,0x2cf6a7bf,0xacf68000,0x2c3527bf,0xa99fab28,0x23e62cad,0x2bd3ab28,0xac76299f,0x2cd7a7bf,0xad0923e6,
0x1fefad0f,0xa5e02cf6,0x28c5acad,0xaa6b2c35,0xaa6bab28,0x28c52c35,0xa5e0acad,0x1fef2cf6,0xad09a90f,0x2cd723e6,0xac76a7bf,0x2bd3299f,
0xaa6bab28,0x28c52c35,0xa5e0acad,0x1fef2cf6,0xad098000,0x2cd723e6,0xac76a7bf,0x2bd3299f,0xabd32b28,0x2c76a99f,0xacd727bf,0x2d09a3e6,
0x9fef290f,0x25e0acf6,0xa8c52cad,0x2a6bac35,0x8000290f,0xad0f,0x80002d0f,0xad0f,0x80002d0f,0xad0f,0x80002d0f,0xad0f,
0x80002d0f,0xad0f,0x80002d0f,0xad0f,0x80002d0f,0xad0f,0x80002d0f,0xad0f,0xad0f290f,0x2d0f0000,0xad0f0000,0x2d0f0000,
0xad0f0000,0x2d0f0000,0xad0f0000,0x2d0f0000,0xad0f0000,0x2d0f0000,0xad0f0000,0x2d0f0000,0xad0f0000,0x2d0f0000,0xad0f0000,0x2d0f0000,
0x2bd32b28,0xac76a99f,0x2cd727bf,0xad09a3e6,0x1fef290f,0xa5e0acf6,0x28c52cad,0xaa6bac35,0x2a6bab28,0xa8c52c35,0x25e0acad,0x9fef2cf6,
0x2d090000,0xacd723e6,0x2c76a7bf,0xabd3299f,0xaa6b2b28,0x28c5ac35,0xa5e02cad,0x1fefacf6,0xad09a90f,0x2cd7a3e6,0xac7627bf,0x2bd3a99f,
0x2bd32b28,0xac76a99f,0x2cd727bf,0xad09a3e6,0x1fef2d0f,0xa5e0acf6,0x28c52cad,0xaa6bac35,0xa3e6ad0f,0x299f2cad,0xac35ab28,0x2cf627bf,
0xacf68000,0x2c35a7bf,0xa99f2b28,0x23e6acad,0x23e6290f,0xa99facad,0x2c352b28,0xacf6a7bf,0x2cf60000,0xac3527bf,0x299fab28,0xa3e62cad,
0x2cf60000,0xac3527bf,0x299fab28,0xa3e62cad,0xa3e6ad0f,0x299f2cad,0xac35ab28,0x2cf627bf,0xacf6290f,0x2c35a7bf,0xa99f2b28,0x23e6acad,
0x23e62d0f,0xa99facad,0x2c352b28,0xacf6a7bf,0x2c762b28,0xad09a3e6,0x2bd3a7bf,0xa5e02c35,0xacd78000,0x2a6ba99f,0x9fef2cad,0xa8c5acf6,
0x28c5ab28,0x1fef2cf6,0xaa6bacad,0x2cd7299f,0x25e0290f,0xabd3ac35,0x2d0927bf,0xac7623e6,0xa8c52b28,0x9fefacf6,0x2a6b2cad,0xacd7a99f,
0xa5e0ad0f,0x2bd32c35,0xad09a7bf,0x2c76a3e6,0x2c762b28,0xad09a3e6,0x2bd3a7bf,0xa5e02c35,0xacd7a90f,0x2a6ba99f,0x9fef2cad,0xa8c5acf6,
0xacad290f,0x27bfab28,0x27bf2d0f,0xacadab28,0x2cad0000,0xa7bf2b28,0xa7bfad0f,0x2cad2b28,0xacad0000,0x27bfab28,0x27bf2d0f,0xacadab28,
0x2cad0000,0xa7bf2b28,0xa7bfad0f,0x2cad2b28,0x27bf290f,0xacadab28,0x2cad0000,0xa7bf2b28,0xa7bfad0f,0x2cad2b28,0xacad8000,0x27bfab28,
0x27bf2d0f,0xacadab28,0x2cad0000,0xa7bf2b28,0xa7bfad0f,0x2cad2b28,0xacad8000,0x27bfab28,0x25e0ab28,0x2a6b2cf6,0xad09a7bf,0x28c5a99f,
0xac76a90f,0x1fefac35,0x2bd32cad,0xacd7a3e6,0xacd7ab28,0x2bd3a3e6,0x1fef2cad,0xac76ac35,0x28c52d0f,0xad09a99f,0x2a6ba7bf,0x25e02cf6,
0xacd7ab28,0x2bd3a3e6,0x1fef2cad,0xac76ac35,0x28c5290f,0xad09a99f,0x2a6ba7bf,0x25e02cf6,0xa5e02b28,0xaa6bacf6,0x2d0927bf,0xa8c5299f,
0x2c760000,0x9fef2c35,0xabd3acad,0x2cd723e6,0x2c350000,0x23e62cad,0xacf6ab28,0x299fa7bf,0x299f2d0f,0xacf6a7bf,0x23e6ab28,0x2c352cad,
0xac35290f,0xa3e6acad,0x2cf62b28,0xa99f27bf,0xa99fad0f,0x2cf627bf,0xa3e62b28,0xac35acad,0xa99fad0f,0x2cf627bf,0xa3e62b28,0xac35acad,
0x2c350000,0x23e62cad,0xacf6ab28,0x299fa7bf,0x299f290f,0xacf6a7bf,0x23e6ab28,0x2c352cad,0xac358000,0xa3e6acad,0x2cf62b28,0xa99f27bf,
0x1fefab28,0x2cd72c35,0xa8c527bf,0xabd3acf6,0xaa6bad0f,0x2c7623e6,0x25e02cad,0xad09a99f,0xad09ab28,0x25e0a99f,0x2c762cad,0xaa6b23e6,
0xabd3a90f,0xa8c5acf6,0x2cd727bf,0x1fef2c35,0xad09ab28,0x25e0a99f,0x2c762cad,0xaa6b23e6,0xabd38000,0xa8c5acf6,0x2cd727bf,0x1fef2c35,
0x9fef2b28,0xacd7ac35,0x28c5a7bf,0x2bd32cf6,0x2a6b290f,0xac76a3e6,0xa5e0acad,0x2d09299f,0x2b28290f,0xab288000,0xab28ad0f,0x2b280000,
0x2b282d0f,0xab288000,0xab28ad0f,0x2b280000,0x2b282d0f,0xab288000,0xab28ad0f,0x2b280000,0x2b282d0f,0xab288000,0xab28ad0f,0x2b280000,
0xab28290f,0xab28ad0f,0x2b280000,0x2b282d0f,0xab280000,0xab28ad0f,0x2b280000,0x2b282d0f,0xab280000,0xab28ad0f,0x2b280000,0x2b282d0f,
0xab280000,0xab28ad0f,0x2b280000,0x2b282d0f,0x2d092b28,0x25e02c35,0xac76a7bf,0xaa6bacf6,0x2bd3290f,0xa8c523e6,0xacd7acad,0x1fefa99f,
0x9fefab28,0x2cd7299f,0x28c52cad,0xabd3a3e6,0x2a6b0000,0x2c762cf6,0xa5e027bf,0xad09ac35,0x1fef2b28,0xacd7a99f,0xa8c5acad,0x2bd323e6,
0xaa6ba90f,0xac76acf6,0x25e0a7bf,0x2d092c35,0x2d092b28,0x25e02c35,0xac76a7bf,0xaa6bacf6,0x2bd32d0f,0xa8c523e6,0xacd7acad,0x1fefa99f,
0xac35ad0f,0x23e6a7bf,0x2cf62b28,0x299f2cad,0xa99f8000,0xacf6acad,0xa3e6ab28,0x2c3527bf,0x2c35290f,0xa3e627bf,0xacf6ab28,0xa99facad,
0x299f0000,0x2cf62cad,0x23e62b28,0xac35a7bf,0x299f0000,0x2cf62cad,0x23e62b28,0xac35a7bf,0xac35ad0f,0x23e6a7bf,0x2cf62b28,0x299f2cad,
0xa99f290f,0xacf6acad,0xa3e6ab28,0x2c3527bf,0x2c352d0f,0xa3e627bf,0xacf6ab28,0xa99facad,0x2cd72b28,0x2bd32cf6,0x9fef27bf,0xac76a99f,
0xa8c58000,0xad09ac35,0xaa6bacad,0x25e0a3e6,0xa5e0ab28,0x2a6b23e6,0x2d092cad,0x28c52c35,0x2c76290f,0x1fef299f,0xabd3a7bf,0xacd7acf6,
0x25e02b28,0xaa6ba3e6,0xad09acad,0xa8c5ac35,0xac76ad0f,0x9fefa99f,0x2bd327bf,0x2cd72cf6,0x2cd72b28,0x2bd32cf6,0x9fef27bf,0xac76a99f,
0xa8c5a90f,0xad09ac35,0xaa6bacad,0x25e0a3e6,0xa7bf290f,0xacadab28,0xacadad0f,0xa7bfab28,0x27bf0000,0x2cad2b28,0x2cad2d0f,0x27bf2b28,
0xa7bf0000,0xacadab28,0xacadad0f,0xa7bfab28,0x27bf0000,0x2cad2b28,0x2cad2d0f,0x27bf2b28,0x2cad290f,0x27bf2b28,0xa7bf8000,0xacadab28,
0xacadad0f,0xa7bfab28,0x27bf0000,0x2cad2b28,0x2cad2d0f,0x27bf2b28,0xa7bf8000,0xacadab28,0xacadad0f,0xa7bfab28,0x27bf0000,0x2cad2b28,
0xa8c5ab28,0x1fefa3e6,0x2a6b27bf,0x2cd72c35,0xa5e0a90f,0xabd3a99f,0xad09acad,0xac76acf6,0xac76ab28,0xad09acf6,0xabd3acad,0xa5e0a99f,
0x2cd72d0f,0x2a6b2c35,0x1fef27bf,0xa8c5a3e6,0xac76ab28,0xad09acf6,0xabd3acad,0xa5e0a99f,0x2cd7290f,0x2a6b2c35,0x1fef27bf,0xa8c5a3e6,
0x28c52b28,0x9fef23e6,0xaa6ba7bf,0xacd7ac35,0x25e00000,0x2bd3299f,0x2d092cad,0x2c762cf6,0x23e60000,0x299f27bf,0x2c352b28,0x2cf62cad,
0x2cf62d0f,0x2c352cad,0x299f2b28,0x23e627bf,0xa3e6290f,0xa99fa7bf,0xac35ab28,0xacf6acad,0xacf6ad0f,0xac35acad,0xa99fab28,0xa3e6a7bf,
0xacf6ad0f,0xac35acad,0xa99fab28,0xa3e6a7bf,0x23e60000,0x299f27bf,0x2c352b28,0x2cf62cad,0x2cf6290f,0x2c352cad,0x299f2b28,0x23e627bf,
0xa3e68000,0xa99fa7bf,0xac35ab28,0xacf6acad,0xaa6bab28,0xa8c5a99f,0xa5e0a7bf,0x9fefa3e6,0xad09ad0f,0xacd7acf6,0xac76acad,0xabd3ac35,
0xabd3ab28,0xac76ac35,0xacd7acad,0xad09acf6,0x9fefa90f,0xa5e0a3e6,0xa8c5a7bf,0xaa6ba99f,0xabd3ab28,0xac76ac35,0xacd7acad,0xad09acf6,
0x9fef8000,0xa5e0a3e6,0xa8c5a7bf,0xaa6ba99f,0x2a6b2b28,0x28c5299f,0x25e027bf,0x1fef23e6,0x2d09290f,0x2cd72cf6,0x2c762cad,0x2bd32c35,
0x39a839a8,0x0,0x39a139a8,0xac700000,0x39a839a8,0x0,0x396a398c,0xb292b06a,0x39a839a8,0x0,0x38fd393a,0xb555b454,
0x39a839a8,0x0,0x385f38b4,0xb72db649,0x39a839a8,0x98710000,0x39a139a8,0xac930000,0x39a839a8,0x9eaa9c71,0x3966398b,0xb2c4b08d,
0x39a839a8,0xa18ea071,0x38f33933,0xb57cb475,0x39a839a8,0xa3c6a2aa,0x384b38a5,0xb75db675,0x39a839a8,0x9c710000,0x39a039a8,0xacb60000,
0x39a839a8,0xa2aaa071,0x39623989,0xb2f7b0b0,0x39a739a8,0xa58da471,0x38e8392c,0xb5a3b496,0x39a739a7,0xa7c6a6aa,0x38373896,0xb78cb6a1,
0x39a839a8,0x9eaa0000,0x39a039a8,0xacda0000,0x39a839a8,0xa4ffa2aa,0x395e3987,0xb32ab0d2,0x39a739a7,0xa82aa6aa,0x38dc3925,0xb5c9b4b6,
0x39a539a6,0xa9d4a8ff,0x38223886,0xb7bab6cc,0x39a839a8,0xa0710000,0x399f39a8,0xacfd0000,0x39a739a8,0xa6aaa471,0x39593985,0xb35cb0f5,
0x39a539a6,0xa98da871,0x38d1391d,0xb5efb4d6,0x39a339a4,0xabc4aaa9,0x380c3876,0xb7e7b6f6,0x39a839a8,0xa18e0000,0x399f39a8,0xad200000,
0x39a739a7,0xa82aa58d,0x39553983,0xb38fb118,0x39a439a5,0xaaefa98d,0x38c53915,0xb615b4f6,0x39a039a2,0xacdaac29,0x37ed3865,0xb809b720,
0x39a839a8,0xa2aa0000,0x399e39a8,0xad440000,0x39a639a7,0xa8ffa6aa,0x39503981,0xb3c1b13a,0x39a239a4,0xac29aaa9,0x38b9390e,0xb63ab516,
0x399c399f,0xadd1acfd,0x37c03854,0xb81fb749,0x39a839a8,0xa3c60000,0x399e39a8,0xad670000,0x39a539a7,0xa9d4a7c6,0x394c397f,0xb3f3b15d,
0x39a039a3,0xacdaabc4,0x38ad3905,0xb65fb536,0x3998399c,0xaec7add1,0x37923843,0xb834b771,0x39a839a8,0xa4710000,0x399d39a8,0xad8a0000,
0x39a439a6,0xaaa9a871,0x3947397d,0xb412b17f,0x399d39a1,0xad8aac70,0x38a038fd,0xb684b555,0x39933998,0xafbdaea4,0x37643831,0xb849b799,
0x39a839a8,0xa4ff0000,0x399d39a8,0xadad0000,0x39a339a6,0xab7da8ff,0x3942397b,0xb42bb1a2,0x399a399f,0xae3aacfd,0x389338f5,0xb6a8b575,
0x398d3994,0xb059af77,0x3734381f,0xb85db7c0,0x39a739a8,0xa58d0000,0x399c39a8,0xadd10000,0x39a239a5,0xac29a98d,0x393d3978,0xb444b1c4,
0x3997399d,0xaeeaad8a,0x388638ec,0xb6ccb594,0x39873990,0xb0d2b024,0x3704380c,0xb870b7e7,0x39a739a8,0xa61c0000,0x399c39a8,0xadf40000,
0x39a139a5,0xac93aa1b,0x39383976,0xb45db1e7,0x3994399b,0xaf9aae17,0x387838e3,0xb6efb5b2,0x3980398b,0xb14cb08d,0x36d337f3,0xb883b806,
0x39a739a8,0xa6aa0000,0x399b39a8,0xae170000,0x399f39a4,0xacfdaaa9,0x39333974,0xb475b209,0x39903998,0xb024aea4,0x386b38da,0xb712b5d1,
0x39783985,0xb1c4b0f5,0x36a137cd,0xb896b819,0x39a739a8,0xa7380000,0x399a39a8,0xae3a0000,0x399e39a4,0xad67ab36,0x392e3971,0xb48eb22b,
0x398b3996,0xb07caf30,0x385d38d1,0xb734b5ef,0x3970397f,0xb23cb15d,0x366e37a6,0xb8a8b82b,0x39a739a8,0xa7c60000,0x399a39a8,0xae5e0000,
0x399c39a3,0xadd1abc4,0x3928396f,0xb4a6b24d,0x39873993,0xb0d2afbd,0x384e38c7,0xb756b60e,0x39673978,0xb2b3b1c4,0x363a377f,0xb8b9b83d,
0x39a739a8,0xa82a0000,0x399939a8,0xae810000,0x399a39a2,0xae3aac29,0x3923396c,0xb4beb26f,0x39823990,0xb129b024,0x384038be,0xb778b62b,
0x395e3971,0xb32ab22b,0x36063756,0xb8cab84e,0x39a639a8,0xa8710000,0x399839a8,0xaea40000,0x399839a1,0xaea4ac70,0x391d396a,0xb4d6b292,
0x397d398c,0xb17fb06a,0x383138b4,0xb799b649,0x3954396a,0xb39fb292,0x35d1372d,0xb8dab85f,0x39a639a8,0xa8b80000,0x399839a8,0xaec70000,
0x399639a0,0xaf0dacb6,0x39173967,0xb4eeb2b3,0x39773989,0xb1d6b0b0,0x382238aa,0xb7bab667,0x39493962,0xb40ab2f7,0x359b3704,0xb8eab870,
0x39a639a8,0xa8ff0000,0x399739a8,0xaeea0000,0x3994399f,0xaf77acfd,0x39113965,0xb506b2d5,0x39713985,0xb22bb0f5,0x381338a0,0xb7dab684,
0x393d3959,0xb444b35c,0x356536da,0xb8f9b880,0x39a639a8,0xa9460000,0x399639a8,0xaf0d0000,0x3992399e,0xafe0ad44,0x390c3962,0xb51eb2f7,
0x396b3981,0xb280b13a,0x38033896,0xb7fab6a1,0x39313950,0xb47db3c1,0x352e36af,0xb907b890,0x39a539a8,0xa98d0000,0x399639a8,0xaf300000,
0x3990399d,0xb024ad8a,0x3905395f,0xb536b319,0x3965397d,0xb2d5b17f,0x37e7388b,0xb80cb6bd,0x39253947,0xb4b6b412,0x34f63684,0xb915b8a0,
0x39a539a8,0xa9d40000,0x399539a8,0xaf530000,0x398d399c,0xb059add1,0x38ff395c,0xb54db33b,0x395e3978,0xb32ab1c4,0x37c73880,0xb81cb6da,
0x3917393d,0xb4eeb444,0x34be3658,0xb923b8af,0x39a539a8,0xaa1b0000,0x399439a8,0xaf770000,0x398b399b,0xb08dae17,0x38f93959,0xb565b35c,
0x39563974,0xb37eb209,0x37a63876,0xb82bb6f6,0x390a3933,0xb526b475,0x3485362b,0xb92fb8be,0x39a539a8,0xaa620000,0x399439a8,0xaf9a0000,
0x3988399a,0xb0c1ae5e,0x38f33956,0xb57cb37e,0x394f396f,0xb3d2b24d,0x3785386b,0xb83ab712,0x38fb3928,0xb55db4a6,0x344c35fe,0xb93cb8cc,
0x39a439a8,0xaaa90000,0x399339a8,0xafbd0000,0x39853998,0xb0f5aea4,0x38ec3954,0xb594b39f,0x3947396a,0xb412b292,0x3764385f,0xb849b72d,
0x38ec391d,0xb594b4d6,0x341235d1,0xb947b8da,0x39a439a8,0xaaef0000,0x399239a8,0xafe00000,0x39823997,0xb129aeea,0x38e53950,0xb5abb3c1,
0x393f3965,0xb43cb2d5,0x37423854,0xb857b749,0x38dc3911,0xb5c9b506,0x33b035a3,0xb952b8e8,0x39a439a8,0xab360000,0x399139a8,0xb0010000,
0x397f3996,0xb15daf30,0x38df394d,0xb5c2b3e2,0x3936395f,0xb465b319,0x37203849,0xb865b764,0x38cc3905,0xb5feb536,0x333b3575,0xb95cb8f5,
0x39a339a8,0xab7d0000,0x399039a8,0xb0130000,0x397c3994,0xb191af77,0x38d8394a,0xb5d9b402,0x392e3959,0xb48eb35c,0x36fd383d,0xb873b77f,
0x38bb38f9,0xb633b565,0x32c43546,0xb966b901,0x39a339a8,0xabc40000,0x399039a8,0xb0240000,0x39783993,0xb1c4afbd,0x38d13947,0xb5efb412,
0x39253954,0xb4b6b39f,0x36da3831,0xb880b799,0x38aa38ec,0xb667b594,0x324d3516,0xb96fb90e,0x39a239a8,0xac050000,0x398f39a8,0xb0360000,
0x39753991,0xb1f8b001,0x38ca3944,0xb606b423,0x391b394d,0xb4deb3e2,0x36b63825,0xb88eb7b3,0x389838df,0xb699b5c2,0x31d634e6,0xb977b919,
0x39a239a8,0xac290000,0x398e39a8,0xb0470000,0x39713990,0xb22bb024,0x38c33941,0xb61db433,0x39113947,0xb506b412,0x36923819,0xb89bb7cd,
0x388638d1,0xb6ccb5ef,0x315d34b6,0xb97fb925,0x39a239a8,0xac4c0000,0x398d39a8,0xb0590000,0x396e398e,0xb25eb047,0x38bb393d,0xb633b444,
0x39073941,0xb52eb433,0x366e380c,0xb8a8b7e7,0x387338c3,0xb6fdb61d,0x30e43485,0xb986b92f,0x39a839a8,0x0,0x372d3800,0xb85fb800,
0x39a839a8,0x0,0x35553649,0xb8fdb8b4,0x39a839a8,0x0,0x32923454,0xb96ab93a,0x39a839a8,0x0,0x2c70306a,0xb9a1b98c,
0x39a839a8,0xa4ffa471,0x36ef37cd,0xb878b819,0x39a739a7,0xa61ca58d,0x34fe35fe,0xb913b8cc,0x39a739a7,0xa738a6aa,0x31b333e2,0xb979b94d,
0x39a739a7,0xa82aa7c6,0x28b82eea,0xb9a6b997,0x39a639a6,0xa8ffa871,0x36af3799,0xb890b831,0x39a539a5,0xaa1ba98d,0x34a635b2,0xb928b8e3,
0x39a439a4,0xab36aaa9,0x30d23319,0xb987b95f,0x39a239a3,0xac29abc4,0x1c712cfd,0xb9a8b99f,0x39a339a4,0xab7daaa9,0x366e3764,0xb8a8b849,
0x39a139a2,0xac93ac29,0x344c3565,0xb93cb8f9,0x399e399f,0xad67acfd,0x2fe0324d,0xb992b96f,0x399a399c,0xae3aadd1,0xa7382a1b,0xb9a7b9a5,
0x399f39a1,0xacfdac70,0x362b372d,0xb8beb85f,0x399b399d,0xae17ad8a,0x33e23516,0xb94db90e,0x39963998,0xaf30aea4,0x2e17317f,0xb99bb97d,
0x39903993,0xb024afbd,0xabc42471,0xb9a3b9a8,0x399a399d,0xae3aad8a,0x35e836f6,0xb8d3b876,0x39943997,0xaf9aaeea,0x332a34c6,0xb95eb921,
0x398b3990,0xb07cb024,0x2c4c30b0,0xb9a2b989,0x39823987,0xb129b0d2,0xadf4a2aa,0xb99cb9a8,0x39943998,0xaf77aea4,0x35a336bd,0xb8e8b88b,
0x398b3990,0xb08db024,0x326f3475,0xb96cb933,0x397f3985,0xb15db0f5,0x28ff2fbd,0xb9a6b993,0x39713978,0xb22bb1c4,0xb001a98d,0xb991b9a5,
0x398d3993,0xb059afbd,0x355d3684,0xb8fbb8a0,0x39803987,0xb14cb0d2,0x31b33423,0xb979b944,0x39703978,0xb23cb1c4,0x218e2e17,0xb9a8b99b,
0x395e3967,0xb32ab2b3,0xb107acb6,0xb984b9a0,0x3985398c,0xb0f5b06a,0x35163649,0xb90eb8b4,0x3974397d,0xb209b17f,0x30f5339f,0xb985b954,
0x395f396a,0xb319b292,0xa4712c70,0xb9a8b9a1,0x39473954,0xb412b39f,0xb209aea4,0xb974b998,0x397c3985,0xb191b0f5,0x34ce360e,0xb91fb8c7,
0x39663971,0xb2c4b22b,0x303632f7,0xb98fb962,0x394c3959,0xb3f3b35c,0xa9d4298d,0xb9a5b9a5,0x392e393d,0xb48eb444,0xb308b047,0xb960b98e,
0x3971397d,0xb22bb17f,0x348535d1,0xb92fb8da,0x39563965,0xb37eb2d5,0x2eea324d,0xb997b96f,0x39363947,0xb465b412,0xacb62471,0xb9a0b9a8,
0x39113925,0xb506b4b6,0xb402b13a,0xb94ab981,0x39663974,0xb2c4b209,0x343c3594,0xb93fb8ec,0x39463956,0xb41bb37e,0x2d6731a2,0xb99eb97b,
0x391f3933,0xb4ceb475,0xae81a071,0xb999b9a8,0x38f3390a,0xb57cb526,0xb47db22b,0xb931b971,0x3959396a,0xb35cb292,0x33e23555,0xb94db8fd,
0x39333947,0xb475b412,0x2bc430f5,0xb9a3b985,0x3905391d,0xb536b4d6,0xb024a871,0xb990b9a6,0x38d138ec,0xb5efb594,0xb4f6b319,0xb915b95f,
0x394c395f,0xb3f3b319,0x334c3516,0xb95bb90e,0x391f3936,0xb4ceb465,0x28b83047,0xb9a6b98e,0x38ea3905,0xb59bb536,0xb107abc4,0xb984b9a3,
0x38ad38cc,0xb65fb5fe,0xb56db402,0xb8f7b94a,0x393d3954,0xb444b39f,0x32b334d6,0xb967b91d,0x390a3925,0xb526b4b6,0x22aa2f30,0xb9a8b996,
0x38cc38ec,0xb5feb594,0xb1e7ad8a,0xb976b99d,0x388638aa,0xb6ccb667,0xb5e0b475,0xb8d6b933,0x392e3947,0xb48eb412,0x321a3496,0xb973b92c,
0x38f33911,0xb57cb506,0xa18e2dd1,0xb9a8b99c,0x38ad38d1,0xb65fb5ef,0xb2c4af30,0xb966b996,0x385d3886,0xb734b6cc,0xb650b4e6,0xb8b2b919,
0x391d393a,0xb4d6b454,0x317f3454,0xb97db93a,0x38da38fd,0xb5d1b555,0xa8712c70,0xb9a6b9a1,0x388b38b4,0xb6bdb649,0xb39fb06a,0xb954b98c,
0x3831385f,0xb799b72d,0xb6bdb555,0xb88bb8fd,0x390c392c,0xb51eb496,0x30e43412,0xb986b947,0x38c038e8,0xb624b5a3,0xab7d2a1b,0xb9a3b9a5,
0x38683896,0xb719b6a1,0xb43cb13a,0xb93fb981,0x38033837,0xb7fab78c,0xb727b5c2,0xb862b8df,0x38f9391d,0xb565b4d6,0x3047339f,0xb98eb954,
0x38a538d1,0xb675b5ef,0xad4426aa,0xb99eb9a7,0x38433876,0xb771b6f6,0xb4a6b209,0xb928b974,0x37a6380c,0xb82bb7e7,0xb78cb62b,0xb837b8be,
0x38e5390e,0xb5abb516,0x2f533319,0xb995b95f,0x388938b9,0xb6c4b63a,0xaec71c71,0xb998b9a8,0x381c3854,0xb7c7b749,0xb50eb2d5,0xb910b965,
0x374237c0,0xb857b81f,0xb7edb692,0xb809b89b,0x38d138fd,0xb5efb555,0x2e173292,0xb99bb96a,0x386b38a0,0xb712b684,0xb024a471,0xb990b9a8,
0x37e73831,0xb80cb799,0xb575b39f,0xb8f5b954,0x36da3764,0xb880b849,0xb825b6f6,0xb7b3b876,0x38bb38ec,0xb633b594,0x2cda3209,0xb9a0b974,
0x384b3886,0xb75db6cc,0xb0e4a8ff,0xb986b9a6,0x3792380c,0xb834b7e7,0xb5d9b433,0xb8d8b941,0x366e3704,0xb8a8b870,0xb851b756,0xb750b84e,
0x38a538da,0xb675b5d1,0x2b36317f,0xb9a4b97d,0x382b386b,0xb7a6b712,0xb1a2abc4,0xb97bb9a3,0x373b37cd,0xb85ab819,0xb63ab496,0xb8b9b92c,
0x35fe36a1,0xb8ccb896,0xb87bb7b3,0xb6e8b825,0x388e38c7,0xb6b6b60e,0x28b830f5,0xb9a6b985,0x3809384e,0xb7edb756,0xb25ead44,0xb96eb99e,
0x36e1377f,0xb87eb83d,0xb699b4f6,0xb898b915,0x358c363a,0xb8eeb8b9,0xb8a3b806,0xb67cb7f3,0x387638b4,0xb6f6b649,0x2471306a,0xb9a8b98c,
0x37cd3831,0xb819b799,0xb319aea4,0xb95fb998,0x3684372d,0xb8a0b85f,0xb6f6b555,0xb876b8fd,0x351635d1,0xb90eb8da,0xb8c7b831,0xb60eb799,
0x385d38a0,0xb734b684,0x98712fbd,0xb9a8b993,0x37853813,0xb83ab7da,0xb3d2b001,0xb94fb991,0x362436da,0xb8c0b880,0xb750b5b2,0xb851b8e3,
0x349e3565,0xb92ab8f9,0xb8eab85a,0xb59bb73b,0x3843388b,0xb771b6bd,0xa58d2ea4,0xb9a7b998,0x373b37e7,0xb85ab80c,0xb444b0b0,0xb93db989,
0x35c23684,0xb8dfb8a0,0xb7a6b60e,0xb82bb8c7,0x342334f6,0xb944b915,0xb90ab880,0xb526b6da,0x38283876,0xb7adb6f6,0xa9462d8a,0xb9a6b99d,
0x36ef37a6,0xb878b82b,0xb49eb15d,0xb92ab97f,0x355d362b,0xb8fbb8be,0xb7fab667,0xb803b8aa,0x334c3485,0xb95bb92f,0xb926b8a5,0xb4aeb675,
0x380c385f,0xb7e7b72d,0xabc42c70,0xb9a3b9a1,0x36a13764,0xb896b849,0xb4f6b209,0xb915b974,0x34f635d1,0xb915b8da,0xb825b6bd,0xb7b3b88b,
0x324d3412,0xb96fb947,0xb941b8c7,0xb433b60e,0x37e03849,0xb810b764,0xad202aa9,0xb99fb9a4,0x36503720,0xb8b2b865,0xb54db2b3,0xb8ffb967,
0x348e3575,0xb92eb8f5,0xb84bb712,0xb75db86b,0x314c333b,0xb980b95c,0xb958b8e8,0xb36db5a3,0x37a63831,0xb82bb799,0xae5e2871,0xb99ab9a6,
0x35fe36da,0xb8ccb880,0xb5a3b35c,0xb8e8b959,0x34233516,0xb944b90e,0xb870b764,0xb704b849,0x3047324d,0xb98eb96f,0xb96cb905,0xb26fb536,
0x376b3819,0xb846b7cd,0xaf9a2471,0xb994b9a8,0x35ab3692,0xb8e5b89b,0xb5f7b402,0xb8cfb94a,0x336d34b6,0xb958b925,0xb893b7b3,0xb6a8b825,
0x2e81315d,0xb999b97f,0xb97eb921,0xb16eb4c6,0x39a839a8,0x0,0xac700000,0xb9a1b9a8,0x39a839a8,0x0,0xb292b06a,0xb96ab98c,
0x39a839a8,0x0,0xb555b454,0xb8fdb93a,0x39a839a8,0x0,0xb72db649,0xb85fb8b4,0x39a639a6,0xa8b8a871,0xaec7a871,0xb998b9a6,
0x39a639a6,0xa946a8ff,0xb3d2b1a2,0xb94fb97b,0x39a539a5,0xa9d4a98d,0xb5f7b4f6,0xb8cfb915,0x39a539a5,0xaa62aa1b,0xb7c7b6e8,0xb81cb87b,
0x39a039a1,0xacb6ac70,0xb08dac70,0xb98bb9a1,0x399e399f,0xad44acfd,0xb485b2d5,0xb92fb965,0x399c399d,0xadd1ad8a,0xb692b594,0xb89bb8ec,
0x399a399b,0xae5eae17,0xb82bb77f,0xb7a6b83d,0x39963998,0xaf0daea4,0xb1b3aea4,0xb979b998,0x39923994,0xafe0af77,0xb51eb402,0xb90cb94a,
0x398d3990,0xb059b024,0xb727b62b,0xb862b8be,0x3988398b,0xb0c1b08d,0xb86db806,0xb70bb7f3,0x3989398c,0xb0b0b06a,0xb2d5b06a,0xb965b98c,
0x39813985,0xb13ab0f5,0xb5b2b496,0xb8e3b92c,0x3978397d,0xb1c4b17f,0xb7b3b6bd,0xb825b88b,0x396f3974,0xb24db209,0xb8aab849,0xb667b764,
0x3977397d,0xb1d6b17f,0xb3f3b17f,0xb94cb97d,0x396b3971,0xb280b22b,0xb642b526,0xb8b7b90a,0x395e3965,0xb32ab2d5,0xb81cb749,0xb7c7b854,
0x394f3956,0xb3d2b37e,0xb8e1b886,0xb5bab6cc,0x3962396a,0xb2f7b292,0xb485b292,0xb92fb96a,0x39503959,0xb3c1b35c,0xb6ccb5b2,0xb886b8e3,
0x393d3947,0xb444b412,0xb85ab7cd,0xb73bb819,0x39283933,0xb4a6b475,0xb911b8be,0xb506b62b,0x39493954,0xb40ab39f,0xb50eb39f,0xb910b954,
0x3931393d,0xb47db444,0xb750b63a,0xb851b8b9,0x39173925,0xb4eeb4b6,0xb893b825,0xb6a8b7b3,0x38fb390a,0xb55db526,0xb93cb8f0,0xb44cb584,
0x392c393a,0xb496b454,0xb594b454,0xb8ecb93a,0x390e391d,0xb516b4d6,0xb7cdb6bd,0xb819b88b,0x38ec38fd,0xb594b555,0xb8c7b85f,0xb60eb72d,
0x38c738da,0xb60eb5d1,0xb95fb91d,0xb319b4d6,0x390c391d,0xb51eb4d6,0xb615b4d6,0xb8c5b91d,0x38e538f9,0xb5abb565,0xb822b73b,0xb7bab85a,
0x38bb38d1,0xb633b5ef,0xb8f7b896,0xb56db6a1,0x388e38a5,0xb6b6b675,0xb97cb944,0xb191b423,0x38e838fd,0xb5a3b555,0xb692b555,0xb89bb8fd,
0x38b938d1,0xb63ab5ef,0xb85ab7b3,0xb73bb825,0x388638a0,0xb6ccb684,0xb921b8c7,0xb4c6b60e,0x384e386b,0xb756b712,0xb991b965,0xb001b2d5,
0x38c038da,0xb624b5d1,0xb70bb5d1,0xb86db8da,0x388938a5,0xb6c4b675,0xb88eb813,0xb6b6b7da,0x384b386b,0xb75db712,0xb946b8f5,0xb41bb575,
0x3809382b,0xb7edb7a6,0xb9a0b97f,0xacdab15d,0x389638b4,0xb6a1b649,0xb77fb649,0xb83db8b4,0x38543876,0xb749b6f6,0xb8beb849,0xb62bb764,
0x380c3831,0xb7e7b799,0xb965b91d,0xb2d5b4d6,0x377f37cd,0xb83db819,0xb9a7b993,0xa6aaafbd,0x3868388b,0xb719b6bd,0xb7edb6bd,0xb809b88b,
0x381c3843,0xb7c7b771,0xb8eab87b,0xb59bb6e8,0x379237e7,0xb834b80c,0xb97eb941,0xb16eb433,0x36e1373b,0xb87eb85a,0xb9a7b9a0,0x261cacb6,
0x3837385f,0xb78cb72d,0xb82bb72d,0xb7a6b85f,0x37c0380c,0xb81fb7e7,0xb911b8aa,0xb506b667,0x37043764,0xb870b849,0xb991b95f,0xb001b319,
0x363a36a1,0xb8b9b896,0xb9a0b9a7,0x2cb6a6aa,0x38033831,0xb7fab799,0xb85db799,0xb734b831,0x374237a6,0xb857b82b,0xb935b8d6,0xb46db5e0,
0x366e36da,0xb8a8b880,0xb99fb978,0xad20b1c4,0x358c35fe,0xb8eeb8cc,0xb992b9a7,0x2fe0258d,0x37993800,0xb831b800,0xb88bb800,0xb6bdb800,
0x36bd372d,0xb88bb85f,0xb954b8fd,0xb39fb555,0x35d13649,0xb8dab8b4,0xb9a6b98c,0xa871b06a,0x34d63555,0xb91db8fd,0xb97db9a1,0x317f2c70,
0x37273799,0xb862b831,0xb8b7b831,0xb642b799,0x363336af,0xb8bbb890,0xb96eb921,0xb25eb4c6,0x352e35b2,0xb907b8e3,0xb9a8b99b,0x218eae17,
0x341b34a6,0xb946b928,0xb960b994,0x33082f77,0x36af372d,0xb890b85f,0xb8dfb85f,0xb5c2b72d,0x35a3362b,0xb8e8b8be,0xb983b941,0xb118b433,
0x34853516,0xb92fb90e,0xb9a4b9a4,0x2b36aaa9,0x32b333e2,0xb967b94d,0xb93db981,0x3444313a,0x363336bd,0xb8bbb88b,0xb903b88b,0xb53eb6bd,
0x350e35a3,0xb910b8e8,0xb994b95c,0xaf9ab33b,0x33b03475,0xb952b933,0xb999b9a8,0x2e81a071,0x3129326f,0xb982b96c,0xb913b967,0x34fe32b3,
0x35b23649,0xb8e3b8b4,0xb925b8b4,0xb4b6b649,0x34753516,0xb933b90e,0xb99fb974,0xacfdb209,0x324d339f,0xb96fb954,0xb989b9a6,0x30b02871,
0x2f3030f5,0xb996b985,0xb8e3b947,0x35b23412,0x352e35d1,0xb907b8da,0xb942b8da,0xb42bb5d1,0x33b03485,0xb952b92f,0xb9a6b987,0xa8b8b0d2,
0x30e4324d,0xb986b96f,0xb973b99f,0x321a2cfd,0x2c052eea,0xb9a2b997,0xb8adb921,0x365f34c6,0x34a63555,0xb928b8fd,0xb95cb8fd,0xb33bb555,
0x326f33e2,0xb96cb94d,0xb9a8b996,0x1c71af30,0x2eea30f5,0xb997b985,0xb956b993,0x337e2fbd,0x22aa2bc4,0xb9a8b9a3,0xb870b8f5,0x37043575,
0x341b34d6,0xb946b91d,0xb973b91d,0xb21ab4d6,0x312932b3,0xb982b967,0xb9a5b9a0,0x29d4acb6,0x2c052f30,0xb9a2b996,0xb935b981,0x346d313a,
0xa8b822aa,0xb9a6b9a8,0xb82eb8c3,0x37a0361d,0x33193454,0xb95fb93a,0xb985b93a,0xb0f5b454,0x2fbd317f,0xb993b97d,0xb99db9a6,0x2d8aa871,
0x24712c70,0xb9a8b9a1,0xb90eb96a,0x35163292,0xad8aa871,0xb99db9a6,0xb7cdb88b,0x381936bd,0x31f8339f,0xb975b954,0xb994b954,0xaf9ab39f,
0x2d203047,0xb99fb98e,0xb990b9a8,0x30131c71,0xa73826aa,0xb9a7b9a7,0xb8e1b94d,0x35ba33e2,0xb059ad44,0xb98db99e,0xb734b84e,0x385d3756,
0x30d23292,0xb987b96a,0xb99eb96a,0xad44b292,0x28ff2e17,0xb9a6b99b,0xb97fb9a5,0x315d298d,0xacb6a471,0xb9a0b9a8,0xb8afb92c,0x36583496,
0xb1e7b024,0xb976b990,0xb692b80c,0x389b37e7,0x2f53317f,0xb995b97d,0xb9a5b97d,0xa9d4b17f,0x98712b36,0xb9a8b9a4,0xb969b99e,0x32a32d44,
0xaf9aabc4,0xb994b9a3,0xb878b905,0x36ef3536,0xb36db1a2,0xb958b97b,0xb5e8b78c,0x38d33837,0x2cfd306a,0xb99fb98c,0xb9a8b98c,0xa071b06a,
0xa98d2471,0xb9a5b9a8,0xb94db993,0x33e22fbd,0xb13aaea4,0xb981b998,0xb83db8da,0x377f35d1,0xb475b319,0xb933b95f,0xb536b6f6,0x39053876,
0x29462ea4,0xb9a6b998,0xb9a7b998,0x2738aea4,0xad67a58d,0xb99eb9a7,0xb92eb983,0x348e3118,0xb2a3b0b0,0xb969b989,0xb7fab8aa,0x38033667,
0xb52eb444,0xb907b93d,0xb47db658,0x393138af,0x1c712c70,0xb9a8b9a1,0xb9a2b9a1,0x2c29ac70,0xb001abc4,0xb991b9a3,0xb90ab96f,0x3526324d,
0xb402b209,0xb94ab974,0xb771b876,0x384336f6,0xb5e0b4f6,0xb8d6b915,0xb37eb5b2,0x395638e3,0xa82a2871,0xb9a7b9a6,0xb999b9a6,0x2e81a871,
0xb14cae5e,0xb980b99a,0xb8e1b956,0x35ba337e,0xb4aeb35c,0xb926b959,0xb6e1b83d,0x387e377f,0xb68bb5a3,0xb89db8e8,0xb1f8b506,0x39753911,
0x39a839a8,0x0,0xb85fb800,0xb72db800,0x39a839a8,0x0,0xb8fdb8b4,0xb555b649,0x39a839a8,0x0,0xb96ab93a,0xb292b454,
0x39a839a8,0x0,0xb9a1b98c,0xac70b06a,0x39a439a4,0xaaefaaa9,0xb8a3b849,0xb67cb764,0x39a339a4,0xab7dab36,0xb931b8f0,0xb47db584,
0x39a239a3,0xac05abc4,0xb98ab965,0xb09eb2d5,0x39a239a2,0xac4cac29,0xb9a8b9a0,0x9871acb6,0x39973998,0xaeeaaea4,0xb8dfb88b,0xb5c2b6bd,
0x39943996,0xaf77af30,0xb95cb925,0xb33bb4b6,0x39913993,0xb001afbd,0xb99eb985,0xad44b0f5,0x398e3990,0xb047b024,0xb9a2b9a8,0x2c29a071,
0x39823985,0xb129b0f5,0xb913b8c7,0xb4feb60e,0x397c397f,0xb191b15d,0xb97eb950,0xb16eb3c1,0x39753978,0xb1f8b1c4,0xb9a8b99b,0xa4ffae17,
0x396e3971,0xb25eb22b,0xb98fb9a4,0x30362b36,0x3965396a,0xb2d5b292,0xb941b8fd,0xb433b555,0x3959395f,0xb35cb319,0xb996b974,0xaf30b209,
0x394d3954,0xb3e2b39f,0xb9a5b9a6,0x298da871,0x39413947,0xb433b412,0xb96fb993,0x324d2fbd,0x393f3947,0xb43cb412,0xb966b92c,0xb2c4b496,
0x392e3936,0xb48eb465,0xb9a4b98e,0xaaefb047,0x391b3925,0xb4deb4b6,0xb998b9a7,0x2ec726aa,0x39073911,0xb52eb506,0xb942b976,0x342b31e7,
0x3911391d,0xb506b4d6,0xb983b954,0xb118b39f,0x38f93905,0xb565b536,0xb9a8b99f,0x1c71acfd,0x38df38ec,0xb5c2b594,0xb97fb99d,0x315d2d8a,
0x38c338d1,0xb61db5ef,0xb90ab94d,0x352633e2,0x38dc38ec,0xb5c9b594,0xb998b974,0xaec7b209,0x38bb38cc,0xb633b5fe,0xb9a2b9a7,0x2c05a58d,
0x389838aa,0xb699b667,0xb95bb989,0x334c30b0,0x38733886,0xb6fdb6cc,0xb8c5b919,0x361534e6,0x38a038b4,0xb684b649,0xb9a4b98c,0xaaa9b06a,
0x3876388b,0xb6f6b6bd,0xb993b9a6,0x2fbd2871,0x3849385f,0xb764b72d,0xb92cb96a,0x34963292,0x38193831,0xb7cdb799,0xb876b8da,0x36f635d1,
0x385d3876,0xb734b6f6,0xb9a8b99d,0x1871ad8a,0x38283843,0xb7adb771,0xb979b99c,0x31b32dd1,0x37e0380c,0xb810b7e7,0xb8f3b941,0x357c3433,
0x376b37a6,0xb846b82b,0xb81cb890,0x37c736af,0x38133831,0xb7dab799,0xb9a4b9a6,0x2b36a871,0x37a637e7,0xb82bb80c,0xb956b989,0x337e30b0,
0x37203764,0xb865b849,0xb8afb90e,0x36583516,0x369236da,0xb89bb880,0xb771b83d,0x3843377f,0x378537cd,0xb83ab819,0xb996b9a8,0x2f0d2471,
0x36ef373b,0xb878b85a,0xb92ab96c,0x349e326f,0x365036a1,0xb8b2b896,0xb862b8d1,0x372735ef,0x35ab35fe,0xb8e5b8cc,0xb699b7c0,0x3898381f,
0x36da372d,0xb880b85f,0xb981b9a1,0x313a2c70,0x362b3684,0xb8beb8a0,0xb8f5b947,0x35753412,0x357535d1,0xb8f5b8da,0xb80cb88b,0x37e736bd,
0x34b63516,0xb925b90e,0xb5b2b6f6,0x38e33876,0x36243684,0xb8c0b8a0,0xb963b993,0x32e62fbd,0x355d35c2,0xb8fbb8df,0xb8b7b919,0x364234e6,
0x348e34f6,0xb92eb915,0xb75db83d,0x384b377f,0x336d3423,0xb958b944,0xb4beb61d,0x392338c3,0x356535d1,0xb8f9b8da,0xb93db97d,0x3444317f,
0x348534f6,0xb92fb915,0xb870b8e3,0x370435b2,0x333b3412,0xb95cb947,0xb692b7cd,0x389b3819,0x315d324d,0xb97fb96f,0xb37eb536,0x39563905,
0x349e3516,0xb92ab90e,0xb910b95f,0x350e3319,0x334c3423,0xb95bb944,0xb822b8a5,0x37ba3675,0x314c324d,0xb980b96f,0xb5bab712,0x38e1386b,
0x2e813047,0xb999b98e,0xb16eb444,0x397e393d,0x339f3454,0xb954b93a,0xb8dab93a,0x35d13454,0x317f3292,0xb97db96a,0xb799b85f,0x3831372d,
0x2ea4306a,0xb998b98c,0xb4d6b649,0x391d38b4,0x28712c70,0xb9a6b9a1,0xaea4b292,0x3998396a,0x31f83319,0xb975b95f,0xb89db90e,0x368b3516,
0x2f5330d2,0xb995b987,0xb6e1b813,0x387e37da,0x29462cfd,0xb9a6b99f,0xb3d2b575,0x394f38f5,0xa82a1c71,0xb9a7b9a8,0xa8b8b08d,0x39a6398b,
0x3047317f,0xb98eb97d,0xb85ab8da,0x373b35d1,0x2b362e17,0xb9a4b99b,0xb61db77f,0x38c3383d,0xa58d2471,0xb9a7b9a8,0xb1e7b496,0x3976392c,
0xae5eabc4,0xb99ab9a3,0x27c6acfd,0x39a7399f,0x2d202fbd,0xb99fb993,0xb810b8a0,0x37e03684,0x987128ff,0xb9a8b9a6,0xb54db6cc,0x38ff3886,
0xad67a98d,0xb99eb9a5,0xafe0b35c,0x39923959,0xb14cb001,0xb980b991,0x2e3aa2aa,0x399a39a8,0x26aa2c70,0xb9a7b9a1,0xb77fb85f,0x383d372d,
0xabc4a471,0xb9a3b9a8,0xb475b60e,0x393338c7,0xb0b0aea4,0xb989b998,0xabc4b17f,0x39a3397d,0xb35cb209,0xb959b974,0x313a2aa9,0x398139a4,
0xa7382471,0xb9a7b9a8,0xb6d3b819,0x388337cd,0xaf9aacb6,0xb994b9a0,0xb32ab546,0x395e3901,0xb2a3b13a,0xb969b981,0x1871af30,0x39a83996,
0xb4aeb402,0xb926b94a,0x334c2f77,0x395b3994,0xad44a871,0xb99eb9a6,0xb61db799,0x38c33831,0xb1a2b024,0xb97bb990,0xb15db475,0x397f3933,
0xb444b319,0xb93db95f,0x2c29aaa9,0x39a239a4,0xb5a3b4f6,0xb8e8b915,0x34a631c4,0x39283978,0xb059ad8a,0xb98db99d,0xb55db6f6,0x38fb3876,
0xb36db1e7,0xb958b976,0xaf0db33b,0x3996395c,0xb52eb475,0xb907b933,0x30132071,0x399039a8,0xb68bb5e0,0xb89db8d6,0x359b33c1,0x38ea3950,
0xb209b06a,0xb974b98c,0xb496b649,0x392c38b4,0xb496b39f,0xb92cb954,0xaaa9b17f,0x39a4397d,0xb60eb555,0xb8c7b8fd,0x32092c70,0x397439a1,
0xb764b6bd,0xb849b88b,0x368434d6,0x38a0391d,0xb3b0b209,0xb952b974,0xb38fb594,0x395538ec,0xb56db4a6,0xb8f7b928,0x1eaaaf77,0x39a83994,
0xb6e1b62b,0xb87eb8be,0x33f33024,0x394c3990,0xb816b78c,0xb7d4b837,0x375d35c2,0x384b38df,0xb4a6b39f,0xb928b954,0xb1e7b4d6,0x3976391d,
0xb63ab575,0xb8b9b8f5,0x2c29abc4,0x39a239a3,0xb7a6b6f6,0xb82bb876,0x34e63209,0x39193974,0xb870b825,0xb704b7b3,0x381336a1,0x37da3896,
0xb56db496,0xb8f7b92c,0xb036b412,0x398f3947,0xb6fdb63a,0xb873b8b9,0x2fe09c71,0x399239a8,0xb82eb7b3,0xb7a0b825,0x35c933e2,0x38dc394d,
0xb8c0b87b,0xb624b6e8,0x386d3771,0x370b3843,0xb62bb555,0xb8beb8fd,0xacfdb292,0x399f396a,0xb7b3b6f6,0xb825b876,0x31c42aa9,0x397839a4,
0xb880b831,0xb6dab799,0x36a134d6,0x3896391d,0xb905b8c7,0xb536b60e,0x38be3819,0x362b37cd,0xb6e1b60e,0xb87eb8c7,0xa61cb0f5,0x39a73985,
0xb82eb7a6,0xb7a0b82b,0x338f2eea,0x39553997,0xb8cab880,0xb606b6da,0x376b35b2,0x384638e3,0xb93fb90a,0xb43cb526,0x39033870,0x353e3704,
0xb78cb6bd,0xb837b88b,0x27c6aea4,0x39a73998,0xb87bb825,0xb6e8b7b3,0x34a6313a,0x39283981,0xb90ab8c7,0xb526b60e,0x38133684,0x37da38a0,
0xb96cb941,0xb26fb433,0x393d38be,0x3444362b,0xb816b764,0xb7d4b849,0x2d67aaa9,0x399e39a4,0xb8c0b870,0xb624b704,0x357c32f7,0x38f33962,
0xb93fb905,0xb43cb536,0x38683749,0x37193854,0xb98db96c,0xb059b26f,0x396b3901,0x32803546,0x3c003c00,0x0,0x0,0x0,
0x3c003c00,0x0,0x0,0x0,0x3c003c00,0x0,0x0,0x0,0x3c003c00,0x0,0x0,0x0,
0x3bf63bf6,0xae46ae46,0x0,0x0,0x3bf63bf6,0xae46ae46,0x0,0x0,0x3bf63bf6,0xae46ae46,0x0,0x0,
0x3bf63bf6,0xae46ae46,0x0,0x0,0x3bd93bd9,0xb23eb23e,0x0,0x0,0x3bd93bd9,0xb23eb23e,0x0,0x0,
0x3bd93bd9,0xb23eb23e,0x0,0x0,0x3bd93bd9,0xb23eb23e,0x0,0x0,0x3ba83ba8,0xb4a5b4a5,0x0,0x0,
0x3ba83ba8,0xb4a5b4a5,0x0,0x0,0x3ba83ba8,0xb4a5b4a5,0x0,0x0,0x3ba83ba8,0xb4a5b4a5,0x0,0x0,
0x3b643b64,0xb61fb61f,0x0,0x0,0x3b643b64,0xb61fb61f,0x0,0x0,0x3b643b64,0xb61fb61f,0x0,0x0,
0x3b643b64,0xb61fb61f,0x0,0x0,0x3b0e3b0e,0xb78bb78b,0x0,0x0,0x3b0e3b0e,0xb78bb78b,0x0,0x0,
0x3b0e3b0e,0xb78bb78b,0x0,0x0,0x3b0e3b0e,0xb78bb78b,0x0,0x0,0x3aa73aa7,0xb872b872,0x0,0x0,
0x3aa73aa7,0xb872b872,0x0,0x0,0x3aa73aa7,0xb872b872,0x0,0x0,0x3aa73aa7,0xb872b872,0x0,0x0,
0x3a2f3a2f,0xb913b913,0x0,0x0,0x3a2f3a2f,0xb913b913,0x0,0x0,0x3a2f3a2f,0xb913b913,0x0,0x0,
0x3a2f3a2f,0xb913b913,0x0,0x0,0x39a839a8,0xb9a8b9a8,0x0,0x0,0x39a839a8,0xb9a8b9a8,0x0,0x0,
0x39a839a8,0xb9a8b9a8,0x0,0x0,0x39a839a8,0xb9a8b9a8,0x0,0x0,0x39133913,0xba2fba2f,0x0,0x0,
0x39133913,0xba2fba2f,0x0,0x0,0x39133913,0xba2fba2f,0x0,0x0,0x39133913,0xba2fba2f,0x0,0x0,
0x38723872,0xbaa7baa7,0x0,0x0,0x38723872,0xbaa7baa7,0x0,0x0,0x38723872,0xbaa7baa7,0x0,0x0,
0x38723872,0xbaa7baa7,0x0,0x0,0x378b378b,0xbb0ebb0e,0x0,0x0,0x378b378b,0xbb0ebb0e,0x0,0x0,
0x378b378b,0xbb0ebb0e,0x0,0x0,0x378b378b,0xbb0ebb0e,0x0,0x0,0x361f361f,0xbb64bb64,0x0,0x0,
0x361f361f,0xbb64bb64,0x0,0x0,0x361f361f,0xbb64bb64,0x0,0x0,0x361f361f,0xbb64bb64,0x0,0x0,
0x34a534a5,0xbba8bba8,0x0,0x0,0x34a534a5,0xbba8bba8,0x0,0x0,0x34a534a5,0xbba8bba8,0x0,0x0,
0x34a534a5,0xbba8bba8,0x0,0x0,0x323e323e,0xbbd9bbd9,0x0,0x0,0x323e323e,0xbbd9bbd9,0x0,0x0,
0x323e323e,0xbbd9bbd9,0x0,0x0,0x323e323e,0xbbd9bbd9,0x0,0x0,0x2e462e46,0xbbf6bbf6,0x0,0x0,
0x2e462e46,0xbbf6bbf6,0x0,0x0,0x2e462e46,0xbbf6bbf6,0x0,0x0,0x2e462e46,0xbbf6bbf6,0x0,0x0,
0x0,0xbc00bc00,0x0,0x0,0x0,0xbc00bc00,0x0,0x0,0x0,0xbc00bc00,0x0,0x0,
0x0,0xbc00bc00,0x0,0x0,0xae46ae46,0xbbf6bbf6,0x0,0x0,0xae46ae46,0xbbf6bbf6,0x0,0x0,
0xae46ae46,0xbbf6bbf6,0x0,0x0,0xae46ae46,0xbbf6bbf6,0x0,0x0,0xb23eb23e,0xbbd9bbd9,0x0,0x0,
0xb23eb23e,0xbbd9bbd9,0x0,0x0,0xb23eb23e,0xbbd9bbd9,0x0,0x0,0xb23eb23e,0xbbd9bbd9,0x0,0x0,
0xb4a5b4a5,0xbba8bba8,0x0,0x0,0xb4a5b4a5,0xbba8bba8,0x0,0x0,0xb4a5b4a5,0xbba8bba8,0x0,0x0,
0xb4a5b4a5,0xbba8bba8,0x0,0x0,0xb61fb61f,0xbb64bb64,0x0,0x0,0xb61fb61f,0xbb64bb64,0x0,0x0,
0xb61fb61f,0xbb64bb64,0x0,0x0,0xb61fb61f,0xbb64bb64,0x0,0x0,0xb78bb78b,0xbb0ebb0e,0x0,0x0,
0xb78bb78b,0xbb0ebb0e,0x0,0x0,0xb78bb78b,0xbb0ebb0e,0x0,0x0,0xb78bb78b,0xbb0ebb0e,0x0,0x0,
0xb872b872,0xbaa7baa7,0x0,0x0,0xb872b872,0xbaa7baa7,0x0,0x0,0xb872b872,0xbaa7baa7,0x0,0x0,
0xb872b872,0xbaa7baa7,0x0,0x0,0xb913b913,0xba2fba2f,0x0,0x0,0xb913b913,0xba2fba2f,0x0,0x0,
0xb913b913,0xba2fba2f,0x0,0x0,0xb913b913,0xba2fba2f,0x0,0x0,0xb9a8b9a8,0xb9a8b9a8,0x0,0x0,
0xb9a8b9a8,0xb9a8b9a8,0x0,0x0,0xb9a8b9a8,0xb9a8b9a8,0x0,0x0,0xb9a8b9a8,0xb9a8b9a8,0x0,0x0,
0xba2fba2f,0xb913b913,0x0,0x0,0xba2fba2f,0xb913b913,0x0,0x0,0xba2fba2f,0xb913b913,0x0,0x0,
0xba2fba2f,0xb913b913,0x0,0x0,0xbaa7baa7,0xb872b872,0x0,0x0,0xbaa7baa7,0xb872b872,0x0,0x0,
0xbaa7baa7,0xb872b872,0x0,0x0,0xbaa7baa7,0xb872b872,0x0,0x0,0xbb0ebb0e,0xb78bb78b,0x0,0x0,
0xbb0ebb0e,0xb78bb78b,0x0,0x0,0xbb0ebb0e,0xb78bb78b,0x0,0x0,0xbb0ebb0e,0xb78bb78b,0x0,0x0,
0xbb64bb64,0xb61fb61f,0x0,0x0,0xbb64bb64,0xb61fb61f,0x0,0x0,0xbb64bb64,0xb61fb61f,0x0,0x0,
0xbb64bb64,0xb61fb61f,0x0,0x0,0xbba8bba8,0xb4a5b4a5,0x0,0x0,0xbba8bba8,0xb4a5b4a5,0x0,0x0,
0xbba8bba8,0xb4a5b4a5,0x0,0x0,0xbba8bba8,0xb4a5b4a5,0x0,0x0,0xbbd9bbd9,0xb23eb23e,0x0,0x0,
0xbbd9bbd9,0xb23eb23e,0x0,0x0,0xbbd9bbd9,0xb23eb23e,0x0,0x0,0xbbd9bbd9,0xb23eb23e,0x0,0x0,
0xbbf6bbf6,0xae46ae46,0x0,0x0,0xbbf6bbf6,0xae46ae46,0x0,0x0,0xbbf6bbf6,0xae46ae46,0x0,0x0,
0xbbf6bbf6,0xae46ae46,0x0,0x0,0x3c003c00,0x0,0xa00000,0x80e00100,0x3c003c00,0x0,0xa00000,0x80e00100,
0x3c003c00,0x0,0xa00000,0x80e00100,0x3c003c00,0x0,0xa00000,0x80e00100,0x3bfe3bfe,0xaa48aa48,0x4180ff,0x813f0001,
0x3bfe3bfe,0xaa48aa48,0x4180ff,0x813f0001,0x3bfe3bfe,0xaa48aa48,0x4180ff,0x813f0001,0x3bfe3bfe,0xaa48aa48,0x4180ff,0x813f0001,
0x3bf63bf6,0xae46ae46,0x80be0082,0x4280fe,0x3bf63bf6,0xae46ae46,0x80be0082,0x4280fe,0x3bf63bf6,0xae46ae46,0x80be0082,0x4280fe,
0x3bf63bf6,0xae46ae46,0x80be0082,0x4280fe,0x3bea3bea,0xb0b2b0b2,0xc3807d,0x80bd0083,0x3bea3bea,0xb0b2b0b2,0xc3807d,0x80bd0083,
0x3bea3bea,0xb0b2b0b2,0xc3807d,0x80bd0083,0x3bea3bea,0xb0b2b0b2,0xc3807d,0x80bd0083,0x3bd93bd9,0xb23eb23e,0x803c0104,0xc4807c,
0x3bd93bd9,0xb23eb23e,0x803c0104,0xc4807c,0x3bd93bd9,0xb23eb23e,0x803c0104,0xc4807c,0x3bd93bd9,0xb23eb23e,0x803c0104,0xc4807c,
0x3bc33bc3,0xb3c6b3c6,0x813b0005,0x803b0105,0x3bc33bc3,0xb3c6b3c6,0x813b0005,0x803b0105,0x3bc33bc3,0xb3c6b3c6,0x813b0005,0x803b0105,
0x3bc33bc3,0xb3c6b3c6,0x813b0005,0x803b0105,0x3ba83ba8,0xb4a5b4a5,0x4680fa,0x813a0006,0x3ba83ba8,0xb4a5b4a5,0x4680fa,0x813a0006,
0x3ba83ba8,0xb4a5b4a5,0x4680fa,0x813a0006,0x3ba83ba8,0xb4a5b4a5,0x4680fa,0x813a0006,0x3b883b88,0xb564b564,0x80b90087,0x4780f9,
0x3b883b88,0xb564b564,0x80b90087,0x4780f9,0x3b883b88,0xb564b564,0x80b90087,0x4780f9,0x3b883b88,0xb564b564,0x80b90087,0x4780f9,
0x3b643b64,0xb61fb61f,0xc88078,0x80b80088,0x3b643b64,0xb61fb61f,0xc88078,0x80b80088,0x3b643b64,0xb61fb61f,0xc88078,0x80b80088,
0x3b643b64,0xb61fb61f,0xc88078,0x80b80088,0x3b3b3b3b,0xb6d7b6d7,0x80370109,0xc98077,0x3b3b3b3b,0xb6d7b6d7,0x80370109,0xc98077,
0x3b3b3b3b,0xb6d7b6d7,0x80370109,0xc98077,0x3b3b3b3b,0xb6d7b6d7,0x80370109,0xc98077,0x3b0e3b0e,0xb78bb78b,0x8136000a,0x8036010a,
0x3b0e3b0e,0xb78bb78b,0x8136000a,0x8036010a,0x3b0e3b0e,0xb78bb78b,0x8136000a,0x8036010a,0x3b0e3b0e,0xb78bb78b,0x8136000a,0x8036010a,
0x3add3add,0xb81db81d,0x4b80f5,0x8135000b,0x3add3add,0xb81db81d,0x4b80f5,0x8135000b,0x3add3add,0xb81db81d,0x4b80f5,0x8135000b,
0x3add3add,0xb81db81d,0x4b80f5,0x8135000b,0x3aa73aa7,0xb872b872,0x80b4008c,0x4c80f4,0x3aa73aa7,0xb872b872,0x80b4008c,0x4c80f4,
0x3aa73aa7,0xb872b872,0x80b4008c,0x4c80f4,0x3aa73aa7,0xb872b872,0x80b4008c,0x4c80f4,0x3a6d3a6d,0xb8c4b8c4,0xcd8073,0x80b3008d,
0x3a6d3a6d,0xb8c4b8c4,0xcd8073,0x80b3008d,0x3a6d3a6d,0xb8c4b8c4,0xcd8073,0x80b3008d,0x3a6d3a6d,0xb8c4b8c4,0xcd8073,0x80b3008d,
0x3a2f3a2f,0xb913b913,0x8032010e,0xce8072,0x3a2f3a2f,0xb913b913,0x8032010e,0xce8072,0x3a2f3a2f,0xb913b913,0x8032010e,0xce8072,
0x3a2f3a2f,0xb913b913,0x8032010e,0xce8072,0x39ed39ed,0xb95fb95f,0x8131000f,0x8031010f,0x39ed39ed,0xb95fb95f,0x8131000f,0x8031010f,
0x39ed39ed,0xb95fb95f,0x8131000f,0x8031010f,0x39ed39ed,0xb95fb95f,0x8131000f,0x8031010f,0x39a839a8,0xb9a8b9a8,0x5080f0,0x81300010,
0x39a839a8,0xb9a8b9a8,0x5080f0,0x81300010,0x39a839a8,0xb9a8b9a8,0x5080f0,0x81300010,0x39a839a8,0xb9a8b9a8,0x5080f0,0x81300010,
0x395f395f,0xb9edb9ed,0x80af0091,0x5180ef,0x395f395f,0xb9edb9ed,0x80af0091,0x5180ef,0x395f395f,0xb9edb9ed,0x80af0091,0x5180ef,
0x395f395f,0xb9edb9ed,0x80af0091,0x5180ef,0x39133913,0xba2fba2f,0xd2806e,0x80ae0092,0x39133913,0xba2fba2f,0xd2806e,0x80ae0092,
0x39133913,0xba2fba2f,0xd2806e,0x80ae0092,0x39133913,0xba2fba2f,0xd2806e,0x80ae0092,0x38c438c4,0xba6dba6d,0x802d0113,0xd3806d,
0x38c438c4,0xba6dba6d,0x802d0113,0xd3806d,0x38c438c4,0xba6dba6d,0x802d0113,0xd3806d,0x38c438c4,0xba6dba6d,0x802d0113,0xd3806d,
0x38723872,0xbaa7baa7,0x812c0014,0x802c0114,0x38723872,0xbaa7baa7,0x812c0014,0x802c0114,0x38723872,0xbaa7baa7,0x812c0014,0x802c0114,
0x38723872,0xbaa7baa7,0x812c0014,0x802c0114,0x381d381d,0xbaddbadd,0x5580eb,0x812b0015,0x381d381d,0xbaddbadd,0x5580eb,0x812b0015,
0x381d381d,0xbaddbadd,0x5580eb,0x812b0015,0x381d381d,0xbaddbadd,0x5580eb,0x812b0015,0x378b378b,0xbb0ebb0e,0x80aa0096,0x5680ea,
0x378b378b,0xbb0ebb0e,0x80aa0096,0x5680ea,0x378b378b,0xbb0ebb0e,0x80aa0096,0x5680ea,0x378b378b,0xbb0ebb0e,0x80aa0096,0x5680ea,
0x36d736d7,0xbb3bbb3b,0xd78069,0x80a90097,0x36d736d7,0xbb3bbb3b,0xd78069,0x80a90097,0x36d736d7,0xbb3bbb3b,0xd78069,0x80a90097,
0x36d736d7,0xbb3bbb3b,0xd78069,0x80a90097,0x361f361f,0xbb64bb64,0x80280118,0xd88068,0x361f361f,0xbb64bb64,0x80280118,0xd88068,
0x361f361f,0xbb64bb64,0x80280118,0xd88068,0x361f361f,0xbb64bb64,0x80280118,0xd88068,0x35643564,0xbb88bb88,0x81270019,0x80270119,
0x35643564,0xbb88bb88,0x81270019,0x80270119,0x35643564,0xbb88bb88,0x81270019,0x80270119,0x35643564,0xbb88bb88,0x81270019,0x80270119,
0x34a534a5,0xbba8bba8,0x5a80e6,0x8126001a,0x34a534a5,0xbba8bba8,0x5a80e6,0x8126001a,0x34a534a5,0xbba8bba8,0x5a80e6,0x8126001a,
0x34a534a5,0xbba8bba8,0x5a80e6,0x8126001a,0x33c633c6,0xbbc3bbc3,0x80a5009b,0x5b80e5,0x33c633c6,0xbbc3bbc3,0x80a5009b,0x5b80e5,
0x33c633c6,0xbbc3bbc3,0x80a5009b,0x5b80e5,0x33c633c6,0xbbc3bbc3,0x80a5009b,0x5b80e5,0x323e323e,0xbbd9bbd9,0xdc8064,0x80a4009c,
0x323e323e,0xbbd9bbd9,0xdc8064,0x80a4009c,0x323e323e,0xbbd9bbd9,0xdc8064,0x80a4009c,0x323e323e,0xbbd9bbd9,0xdc8064,0x80a4009c,
0x30b230b2,0xbbeabbea,0x8023011d,0xdd8063,0x30b230b2,0xbbeabbea,0x8023011d,0xdd8063,0x30b230b2,0xbbeabbea,0x8023011d,0xdd8063,
0x30b230b2,0xbbeabbea,0x8023011d,0xdd8063,0x2e462e46,0xbbf6bbf6,0x8122001e,0x8022011e,0x2e462e46,0xbbf6bbf6,0x8122001e,0x8022011e,
0x2e462e46,0xbbf6bbf6,0x8122001e,0x8022011e,0x2e462e46,0xbbf6bbf6,0x8122001e,0x8022011e,0x2a482a48,0xbbfebbfe,0x5f80e1,0x8121001f,
0x2a482a48,0xbbfebbfe,0x5f80e1,0x8121001f,0x2a482a48,0xbbfebbfe,0x5f80e1,0x8121001f,0x2a482a48,0xbbfebbfe,0x5f80e1,0x8121001f,
0x200080,0x12000c0,0x80600040,0x0,0x200080,0x12000c0,0x80600040,0x0,0x200080,0x12000c0,0x80600040,0x0,
0x200080,0x12000c0,0x80600040,0x0,0x803f0101,0xc1807f,0x80bf0081,0x0,0x803f0101,0xc1807f,0x80bf0081,0x0,
0x803f0101,0xc1807f,0x80bf0081,0x0,0x803f0101,0xc1807f,0x80bf0081,0x0,0x813e0002,0x803e0102,0xc2807e,0x0,
0x813e0002,0x803e0102,0xc2807e,0x0,0x813e0002,0x803e0102,0xc2807e,0x0,0x813e0002,0x803e0102,0xc2807e,0x0,
0x4380fd,0x813d0003,0x803d0103,0x0,0x4380fd,0x813d0003,0x803d0103,0x0,0x4380fd,0x813d0003,0x803d0103,0x0,
0x4380fd,0x813d0003,0x803d0103,0x0,0x80bc0084,0x4480fc,0x813c0004,0x0,0x80bc0084,0x4480fc,0x813c0004,0x0,
0x80bc0084,0x4480fc,0x813c0004,0x0,0x80bc0084,0x4480fc,0x813c0004,0x0,0xc5807b,0x80bb0085,0x4580fb,0x0,
0xc5807b,0x80bb0085,0x4580fb,0x0,0xc5807b,0x80bb0085,0x4580fb,0x0,0xc5807b,0x80bb0085,0x4580fb,0x0,
0x803a0106,0xc6807a,0x80ba0086,0x0,0x803a0106,0xc6807a,0x80ba0086,0x0,0x803a0106,0xc6807a,0x80ba0086,0x0,
0x803a0106,0xc6807a,0x80ba0086,0x0,0x81390007,0x80390107,0xc78079,0x0,0x81390007,0x80390107,0xc78079,0x0,
0x81390007,0x80390107,0xc78079,0x0,0x81390007,0x80390107,0xc78079,0x0,0x4880f8,0x81380008,0x80380108,0x0,
0x4880f8,0x81380008,0x80380108,0x0,0x4880f8,0x81380008,0x80380108,0x0,0x4880f8,0x81380008,0x80380108,0x0,
0x80b70089,0x4980f7,0x81370009,0x0,0x80b70089,0x4980f7,0x81370009,0x0,0x80b70089,0x4980f7,0x81370009,0x0,
0x80b70089,0x4980f7,0x81370009,0x0,0xca8076,0x80b6008a,0x4a80f6,0x0,0xca8076,0x80b6008a,0x4a80f6,0x0,
0xca8076,0x80b6008a,0x4a80f6,0x0,0xca8076,0x80b6008a,0x4a80f6,0x0,0x8035010b,0xcb8075,0x80b5008b,0x0,
0x8035010b,0xcb8075,0x80b5008b,0x0,0x8035010b,0xcb8075,0x80b5008b,0x0,0x8035010b,0xcb8075,0x80b5008b,0x0,
0x8134000c,0x8034010c,0xcc8074,0x0,0x8134000c,0x8034010c,0xcc8074,0x0,0x8134000c,0x8034010c,0xcc8074,0x0,
0x8134000c,0x8034010c,0xcc8074,0x0,0x4d80f3,0x8133000d,0x8033010d,0x0,0x4d80f3,0x8133000d,0x8033010d,0x0,
0x4d80f3,0x8133000d,0x8033010d,0x0,0x4d80f3,0x8133000d,0x8033010d,0x0,0x80b2008e,0x4e80f2,0x8132000e,0x0,
0x80b2008e,0x4e80f2,0x8132000e,0x0,0x80b2008e,0x4e80f2,0x8132000e,0x0,0x80b2008e,0x4e80f2,0x8132000e,0x0,
0xcf8071,0x80b1008f,0x4f80f1,0x0,0xcf8071,0x80b1008f,0x4f80f1,0x0,0xcf8071,0x80b1008f,0x4f80f1,0x0,
0xcf8071,0x80b1008f,0x4f80f1,0x0,0x80300110,0xd08070,0x80b00090,0x0,0x80300110,0xd08070,0x80b00090,0x0,
0x80300110,0xd08070,0x80b00090,0x0,0x80300110,0xd08070,0x80b00090,0x0,0x812f0011,0x802f0111,0xd1806f,0x0,
0x812f0011,0x802f0111,0xd1806f,0x0,0x812f0011,0x802f0111,0xd1806f,0x0,0x812f0011,0x802f0111,0xd1806f,0x0,
0x5280ee,0x812e0012,0x802e0112,0x0,0x5280ee,0x812e0012,0x802e0112,0x0,0x5280ee,0x812e0012,0x802e0112,0x0,
0x5280ee,0x812e0012,0x802e0112,0x0,0x80ad0093,0x5380ed,0x812d0013,0x0,0x80ad0093,0x5380ed,0x812d0013,0x0,
0x80ad0093,0x5380ed,0x812d0013,0x0,0x80ad0093,0x5380ed,0x812d0013,0x0,0xd4806c,0x80ac0094,0x5480ec,0x0,
0xd4806c,0x80ac0094,0x5480ec,0x0,0xd4806c,0x80ac0094,0x5480ec,0x0,0xd4806c,0x80ac0094,0x5480ec,0x0,
0x802b0115,0xd5806b,0x80ab0095,0x0,0x802b0115,0xd5806b,0x80ab0095,0x0,0x802b0115,0xd5806b,0x80ab0095,0x0,
0x802b0115,0xd5806b,0x80ab0095,0x0,0x812a0016,0x802a0116,0xd6806a,0x0,0x812a0016,0x802a0116,0xd6806a,0x0,
0x812a0016,0x802a0116,0xd6806a,0x0,0x812a0016,0x802a0116,0xd6806a,0x0,0x5780e9,0x81290017,0x80290117,0x0,
0x5780e9,0x81290017,0x80290117,0x0,0x5780e9,0x81290017,0x80290117,0x0,0x5780e9,0x81290017,0x80290117,0x0,
0x80a80098,0x5880e8,0x81280018,0x0,0x80a80098,0x5880e8,0x81280018,0x0,0x80a80098,0x5880e8,0x81280018,0x0,
0x80a80098,0x5880e8,0x81280018,0x0,0xd98067,0x80a70099,0x5980e7,0x0,0xd98067,0x80a70099,0x5980e7,0x0,
0xd98067,0x80a70099,0x5980e7,0x0,0xd98067,0x80a70099,0x5980e7,0x0,0x8026011a,0xda8066,0x80a6009a,0x0,
0x8026011a,0xda8066,0x80a6009a,0x0,0x8026011a,0xda8066,0x80a6009a,0x0,0x8026011a,0xda8066,0x80a6009a,0x0,
0x8125001b,0x8025011b,0xdb8065,0x0,0x8125001b,0x8025011b,0xdb8065,0x0,0x8125001b,0x8025011b,0xdb8065,0x0,
0x8125001b,0x8025011b,0xdb8065,0x0,0x5c80e4,0x8124001c,0x8024011c,0x0,0x5c80e4,0x8124001c,0x8024011c,0x0,
0x5c80e4,0x8124001c,0x8024011c,0x0,0x5c80e4,0x8124001c,0x8024011c,0x0,0x80a3009d,0x5d80e3,0x8123001d,0x0,
0x80a3009d,0x5d80e3,0x8123001d,0x0,0x80a3009d,0x5d80e3,0x8123001d,0x0,0x80a3009d,0x5d80e3,0x8123001d,0x0,
0xde8062,0x80a2009e,0x5e80e2,0x0,0xde8062,0x80a2009e,0x5e80e2,0x0,0xde8062,0x80a2009e,0x5e80e2,0x0,
0xde8062,0x80a2009e,0x5e80e2,0x0,0x8021011f,0xdf8061,0x80a1009f,0x0,0x8021011f,0xdf8061,0x80a1009f,0x0,
0x8021011f,0xdf8061,0x80a1009f,0x0,0x8021011f,0xdf8061,0x80a1009f,0x0,
};

constexpr size_t G_CNT = 0;
constexpr size_t G_STATS = G_CNT + 128 * 128;
constexpr size_t G_EB = G_STATS + 2048 * 8;
constexpr size_t G_Y = G_EB + 128 * 16;
constexpr size_t G_Z = G_Y + 2 * 321 * 8192;
constexpr size_t G_H = G_Z + 321 * 8192;
__device__ __align__(1024) uint8_t g_scr[G_H + 32 * 216 * 1024];

enum { C_EPOCH = 0, C_Y = 2, C_Z = 3, C_H = 56 };

constexpr uint32_t STG_B = 24576, NSTG = 7;
constexpr uint32_t STG2_B = 18432;
constexpr uint32_t O_T = 0, O_S = 20480, O_MSG = 40960;
constexpr uint32_t O_H2 = 9 * STG2_B - 4096;
constexpr uint32_t O_TEMP = NSTG * STG_B;
constexpr uint32_t O_CONST = O_TEMP + 24576;
constexpr uint32_t O_DATA = O_CONST + 8192;
constexpr uint32_t O_M = O_TEMP + 16384;
__host__ __device__ constexpr uint32_t col_y(int c) { return c == 0 ? O_TEMP : O_DATA + (c - 1) * 16384; }
__host__ __device__ constexpr uint32_t col_w(int c) { return c == 2 ? O_CONST : col_y(c) + 8192; }
constexpr uint32_t O_EB = O_DATA + 24576;
constexpr uint32_t O_RQ = O_EB + 128;
constexpr uint32_t O_BAR = O_RQ + 64;
constexpr uint32_t SMEM_BYTES = O_BAR + 512;
enum { B_G2 = 7, B_EMPTY = 16, B_CONST = 32, B_COL0, B_COL1, B_WSLAB, B_X, B_HD, B_EPOCH, B_ZD, B_ZD1, B_ZD2, B_ZIN, B_YS, B_WS, B_TD, B_DF, B_HF, B_H2F, B_Z0F, B_LAST, B_G2GO, B_ST, B_NUM };
constexpr uint32_t O_EPOCH = O_BAR + 8 * B_NUM, O_WMAX = O_EPOCH + 4;
__host__ __device__ constexpr uint32_t bar_count(int l) {
  return l < 32 ? ((l & 16) ? 4 : 1) : (l == B_HD || (l == B_WS && CONV_CONS)) ? 8 : (l == B_YS || l == B_WS || (l >= B_ZD && l <= B_ZD2)) ? 4 : (l == B_COL0 || l == B_TD || l == B_H2F) ? 2 : 1;
}
static_assert(SMEM_BYTES <= 232448, "smem");

constexpr uint32_t HI_128 = (1024 >> 4) | (1u << 30);
constexpr uint32_t HI_64 = (512 >> 4) | (2u << 30);
constexpr uint32_t HI_0K = (1024 >> 4), HI_0A = (128 >> 4);
__device__ __forceinline__ uint32_t dlo(uint32_t addr, uint32_t lbo) { return ((addr & 0x3FFFF) >> 4) | ((lbo >> 4) << 16); }

__device__ __forceinline__ void mma_b112(float (&d)[56], uint32_t a0, uint32_t a1, uint32_t a2, uint32_t a3, uint32_t blo, uint32_t bhi, int sd) {
  asm volatile("{\n.reg .pred p;\n.reg .b64 db;\nmov.b64 db, {%60, %61};\nsetp.ne.b32 p, %62, 0;\n"
    "wgmma.mma_async.sync.aligned.m64n112k16.f32.bf16.bf16 {%0, %1, %2, %3, %4, %5, %6, %7, %8, %9, %10, %11, %12, %13, %14, %15, %16, %17, %18, %19, %20, %21, %22, %23, %24, %25, %26, %27, %28, %29, %30, %31, %32, %33, %34, %35, %36, %37, %38, %39, %40, %41, %42, %43, %44, %45, %46, %47, %48, %49, %50, %51, %52, %53, %54, %55}, {%56, %57, %58, %59}, db, p, 1, 1, 1;\n}\n"
    : "+f"(d[0]), "+f"(d[1]), "+f"(d[2]), "+f"(d[3]), "+f"(d[4]), "+f"(d[5]), "+f"(d[6]), "+f"(d[7]), "+f"(d[8]), "+f"(d[9]), "+f"(d[10]), "+f"(d[11]), "+f"(d[12]), "+f"(d[13]), "+f"(d[14]), "+f"(d[15]), "+f"(d[16]), "+f"(d[17]), "+f"(d[18]), "+f"(d[19]), "+f"(d[20]), "+f"(d[21]), "+f"(d[22]), "+f"(d[23]), "+f"(d[24]), "+f"(d[25]), "+f"(d[26]), "+f"(d[27]), "+f"(d[28]), "+f"(d[29]), "+f"(d[30]), "+f"(d[31]), "+f"(d[32]), "+f"(d[33]), "+f"(d[34]), "+f"(d[35]), "+f"(d[36]), "+f"(d[37]), "+f"(d[38]), "+f"(d[39]), "+f"(d[40]), "+f"(d[41]), "+f"(d[42]), "+f"(d[43]), "+f"(d[44]), "+f"(d[45]), "+f"(d[46]), "+f"(d[47]), "+f"(d[48]), "+f"(d[49]), "+f"(d[50]), "+f"(d[51]), "+f"(d[52]), "+f"(d[53]), "+f"(d[54]), "+f"(d[55])
    : "r"(a0), "r"(a1), "r"(a2), "r"(a3), "r"(blo), "r"(bhi), "r"(sd));
}
__device__ __forceinline__ void mma_b104(float (&d)[56], uint32_t a0, uint32_t a1, uint32_t a2, uint32_t a3, uint32_t blo, uint32_t bhi, int sd) {
  asm volatile("{\n.reg .pred p;\n.reg .b64 db;\nmov.b64 db, {%56, %57};\nsetp.ne.b32 p, %58, 0;\n"
    "wgmma.mma_async.sync.aligned.m64n104k16.f32.bf16.bf16 {%0, %1, %2, %3, %4, %5, %6, %7, %8, %9, %10, %11, %12, %13, %14, %15, %16, %17, %18, %19, %20, %21, %22, %23, %24, %25, %26, %27, %28, %29, %30, %31, %32, %33, %34, %35, %36, %37, %38, %39, %40, %41, %42, %43, %44, %45, %46, %47, %48, %49, %50, %51}, {%52, %53, %54, %55}, db, p, 1, 1, 1;\n}\n"
    : "+f"(d[0]), "+f"(d[1]), "+f"(d[2]), "+f"(d[3]), "+f"(d[4]), "+f"(d[5]), "+f"(d[6]), "+f"(d[7]), "+f"(d[8]), "+f"(d[9]), "+f"(d[10]), "+f"(d[11]), "+f"(d[12]), "+f"(d[13]), "+f"(d[14]), "+f"(d[15]), "+f"(d[16]), "+f"(d[17]), "+f"(d[18]), "+f"(d[19]), "+f"(d[20]), "+f"(d[21]), "+f"(d[22]), "+f"(d[23]), "+f"(d[24]), "+f"(d[25]), "+f"(d[26]), "+f"(d[27]), "+f"(d[28]), "+f"(d[29]), "+f"(d[30]), "+f"(d[31]), "+f"(d[32]), "+f"(d[33]), "+f"(d[34]), "+f"(d[35]), "+f"(d[36]), "+f"(d[37]), "+f"(d[38]), "+f"(d[39]), "+f"(d[40]), "+f"(d[41]), "+f"(d[42]), "+f"(d[43]), "+f"(d[44]), "+f"(d[45]), "+f"(d[46]), "+f"(d[47]), "+f"(d[48]), "+f"(d[49]), "+f"(d[50]), "+f"(d[51])
    : "r"(a0), "r"(a1), "r"(a2), "r"(a3), "r"(blo), "r"(bhi), "r"(sd));
}
__device__ __forceinline__ void mma_b160(float (&d)[80], uint32_t alo, uint32_t ahi, uint32_t blo, uint32_t bhi, int sd) {
  asm volatile("{\n.reg .pred p;\n.reg .b64 da, db;\nmov.b64 da, {%80, %81};\nmov.b64 db, {%82, %83};\nsetp.ne.b32 p, %84, 0;\n"
    "wgmma.mma_async.sync.aligned.m64n160k16.f32.bf16.bf16 {%0, %1, %2, %3, %4, %5, %6, %7, %8, %9, %10, %11, %12, %13, %14, %15, %16, %17, %18, %19, %20, %21, %22, %23, %24, %25, %26, %27, %28, %29, %30, %31, %32, %33, %34, %35, %36, %37, %38, %39, %40, %41, %42, %43, %44, %45, %46, %47, %48, %49, %50, %51, %52, %53, %54, %55, %56, %57, %58, %59, %60, %61, %62, %63, %64, %65, %66, %67, %68, %69, %70, %71, %72, %73, %74, %75, %76, %77, %78, %79}, da, db, p, 1, 1, 0, 1;\n}\n"
    : "+f"(d[0]), "+f"(d[1]), "+f"(d[2]), "+f"(d[3]), "+f"(d[4]), "+f"(d[5]), "+f"(d[6]), "+f"(d[7]), "+f"(d[8]), "+f"(d[9]), "+f"(d[10]), "+f"(d[11]), "+f"(d[12]), "+f"(d[13]), "+f"(d[14]), "+f"(d[15]), "+f"(d[16]), "+f"(d[17]), "+f"(d[18]), "+f"(d[19]), "+f"(d[20]), "+f"(d[21]), "+f"(d[22]), "+f"(d[23]), "+f"(d[24]), "+f"(d[25]), "+f"(d[26]), "+f"(d[27]), "+f"(d[28]), "+f"(d[29]), "+f"(d[30]), "+f"(d[31]), "+f"(d[32]), "+f"(d[33]), "+f"(d[34]), "+f"(d[35]), "+f"(d[36]), "+f"(d[37]), "+f"(d[38]), "+f"(d[39]), "+f"(d[40]), "+f"(d[41]), "+f"(d[42]), "+f"(d[43]), "+f"(d[44]), "+f"(d[45]), "+f"(d[46]), "+f"(d[47]), "+f"(d[48]), "+f"(d[49]), "+f"(d[50]), "+f"(d[51]), "+f"(d[52]), "+f"(d[53]), "+f"(d[54]), "+f"(d[55]), "+f"(d[56]), "+f"(d[57]), "+f"(d[58]), "+f"(d[59]), "+f"(d[60]), "+f"(d[61]), "+f"(d[62]), "+f"(d[63]), "+f"(d[64]), "+f"(d[65]), "+f"(d[66]), "+f"(d[67]), "+f"(d[68]), "+f"(d[69]), "+f"(d[70]), "+f"(d[71]), "+f"(d[72]), "+f"(d[73]), "+f"(d[74]), "+f"(d[75]), "+f"(d[76]), "+f"(d[77]), "+f"(d[78]), "+f"(d[79])
    : "r"(alo), "r"(ahi), "r"(blo), "r"(bhi), "r"(sd));
}
__device__ __forceinline__ void mma_h160k(uint32_t (&d)[40], uint32_t alo, uint32_t ahi, uint32_t blo, uint32_t bhi, int sd) {
  asm volatile("{\n.reg .pred p;\n.reg .b64 da, db;\nmov.b64 da, {%40, %41};\nmov.b64 db, {%42, %43};\nsetp.ne.b32 p, %44, 0;\n"
    "wgmma.mma_async.sync.aligned.m64n160k16.f16.f16.f16 {%0, %1, %2, %3, %4, %5, %6, %7, %8, %9, %10, %11, %12, %13, %14, %15, %16, %17, %18, %19, %20, %21, %22, %23, %24, %25, %26, %27, %28, %29, %30, %31, %32, %33, %34, %35, %36, %37, %38, %39}, da, db, p, 1, 1, 0, 0;\n}\n"
    : "+r"(d[0]), "+r"(d[1]), "+r"(d[2]), "+r"(d[3]), "+r"(d[4]), "+r"(d[5]), "+r"(d[6]), "+r"(d[7]), "+r"(d[8]), "+r"(d[9]), "+r"(d[10]), "+r"(d[11]), "+r"(d[12]), "+r"(d[13]), "+r"(d[14]), "+r"(d[15]), "+r"(d[16]), "+r"(d[17]), "+r"(d[18]), "+r"(d[19]), "+r"(d[20]), "+r"(d[21]), "+r"(d[22]), "+r"(d[23]), "+r"(d[24]), "+r"(d[25]), "+r"(d[26]), "+r"(d[27]), "+r"(d[28]), "+r"(d[29]), "+r"(d[30]), "+r"(d[31]), "+r"(d[32]), "+r"(d[33]), "+r"(d[34]), "+r"(d[35]), "+r"(d[36]), "+r"(d[37]), "+r"(d[38]), "+r"(d[39])
    : "r"(alo), "r"(ahi), "r"(blo), "r"(bhi), "r"(sd));
}
__device__ __forceinline__ void mma_h64n(uint32_t (&d)[16], uint32_t alo, uint32_t ahi, uint32_t blo, uint32_t bhi, int sd) {
  asm volatile("{\n.reg .pred p;\n.reg .b64 da, db;\nmov.b64 da, {%16, %17};\nmov.b64 db, {%18, %19};\nsetp.ne.b32 p, %20, 0;\n"
    "wgmma.mma_async.sync.aligned.m64n64k16.f16.f16.f16 {%0, %1, %2, %3, %4, %5, %6, %7, %8, %9, %10, %11, %12, %13, %14, %15}, da, db, p, 1, 1, 0, 1;\n}\n"
    : "+r"(d[0]), "+r"(d[1]), "+r"(d[2]), "+r"(d[3]), "+r"(d[4]), "+r"(d[5]), "+r"(d[6]), "+r"(d[7]), "+r"(d[8]), "+r"(d[9]), "+r"(d[10]), "+r"(d[11]), "+r"(d[12]), "+r"(d[13]), "+r"(d[14]), "+r"(d[15])
    : "r"(alo), "r"(ahi), "r"(blo), "r"(bhi), "r"(sd));
}
__device__ __forceinline__ void mma_h128n(uint32_t (&d)[32], uint32_t alo, uint32_t ahi, uint32_t blo, uint32_t bhi, int sd) {
  asm volatile("{\n.reg .pred p;\n.reg .b64 da, db;\nmov.b64 da, {%32, %33};\nmov.b64 db, {%34, %35};\nsetp.ne.b32 p, %36, 0;\n"
    "wgmma.mma_async.sync.aligned.m64n128k16.f16.f16.f16 {%0, %1, %2, %3, %4, %5, %6, %7, %8, %9, %10, %11, %12, %13, %14, %15, %16, %17, %18, %19, %20, %21, %22, %23, %24, %25, %26, %27, %28, %29, %30, %31}, da, db, p, 1, 1, 0, 1;\n}\n"
    : "+r"(d[0]), "+r"(d[1]), "+r"(d[2]), "+r"(d[3]), "+r"(d[4]), "+r"(d[5]), "+r"(d[6]), "+r"(d[7]), "+r"(d[8]), "+r"(d[9]), "+r"(d[10]), "+r"(d[11]), "+r"(d[12]), "+r"(d[13]), "+r"(d[14]), "+r"(d[15]), "+r"(d[16]), "+r"(d[17]), "+r"(d[18]), "+r"(d[19]), "+r"(d[20]), "+r"(d[21]), "+r"(d[22]), "+r"(d[23]), "+r"(d[24]), "+r"(d[25]), "+r"(d[26]), "+r"(d[27]), "+r"(d[28]), "+r"(d[29]), "+r"(d[30]), "+r"(d[31])
    : "r"(alo), "r"(ahi), "r"(blo), "r"(bhi), "r"(sd));
}
__device__ __forceinline__ void mma_h64r(uint32_t (&d)[16], uint32_t a0, uint32_t a1, uint32_t a2, uint32_t a3, uint32_t blo, uint32_t bhi, int sd) {
  asm volatile("{\n.reg .pred p;\n.reg .b64 db;\nmov.b64 db, {%20, %21};\nsetp.ne.b32 p, %22, 0;\n"
    "wgmma.mma_async.sync.aligned.m64n64k16.f16.f16.f16 {%0, %1, %2, %3, %4, %5, %6, %7, %8, %9, %10, %11, %12, %13, %14, %15}, {%16, %17, %18, %19}, db, p, 1, 1, 0;\n}\n"
    : "+r"(d[0]), "+r"(d[1]), "+r"(d[2]), "+r"(d[3]), "+r"(d[4]), "+r"(d[5]), "+r"(d[6]), "+r"(d[7]), "+r"(d[8]), "+r"(d[9]), "+r"(d[10]), "+r"(d[11]), "+r"(d[12]), "+r"(d[13]), "+r"(d[14]), "+r"(d[15])
    : "r"(a0), "r"(a1), "r"(a2), "r"(a3), "r"(blo), "r"(bhi), "r"(sd));
}
__device__ __forceinline__ void mma_hf80n(float (&d)[40], uint32_t alo, uint32_t ahi, uint32_t blo, uint32_t bhi, int sd) {
  asm volatile("{\n.reg .pred p;\n.reg .b64 da, db;\nmov.b64 da, {%40, %41};\nmov.b64 db, {%42, %43};\nsetp.ne.b32 p, %44, 0;\n"
    "wgmma.mma_async.sync.aligned.m64n80k16.f32.f16.f16 {%0, %1, %2, %3, %4, %5, %6, %7, %8, %9, %10, %11, %12, %13, %14, %15, %16, %17, %18, %19, %20, %21, %22, %23, %24, %25, %26, %27, %28, %29, %30, %31, %32, %33, %34, %35, %36, %37, %38, %39}, da, db, p, 1, 1, 0, 1;\n}\n"
    : "+f"(d[0]), "+f"(d[1]), "+f"(d[2]), "+f"(d[3]), "+f"(d[4]), "+f"(d[5]), "+f"(d[6]), "+f"(d[7]), "+f"(d[8]), "+f"(d[9]), "+f"(d[10]), "+f"(d[11]), "+f"(d[12]), "+f"(d[13]), "+f"(d[14]), "+f"(d[15]), "+f"(d[16]), "+f"(d[17]), "+f"(d[18]), "+f"(d[19]), "+f"(d[20]), "+f"(d[21]), "+f"(d[22]), "+f"(d[23]), "+f"(d[24]), "+f"(d[25]), "+f"(d[26]), "+f"(d[27]), "+f"(d[28]), "+f"(d[29]), "+f"(d[30]), "+f"(d[31]), "+f"(d[32]), "+f"(d[33]), "+f"(d[34]), "+f"(d[35]), "+f"(d[36]), "+f"(d[37]), "+f"(d[38]), "+f"(d[39])
    : "r"(alo), "r"(ahi), "r"(blo), "r"(bhi), "r"(sd));
}

template <int N> __device__ __forceinline__ void mma_g1(float (&d)[56], const uint32_t (&a)[4], uint32_t b, int sd) {
  if (N == 112) mma_b112(d, a[0], a[1], a[2], a[3], b, HI_128, sd); else mma_b104(d, a[0], a[1], a[2], a[3], b, HI_128, sd);
}

constexpr int SPIN_MAX = 1 << 19;
__device__ __forceinline__ void mbar_init(uint32_t b, uint32_t c) { asm volatile("mbarrier.init.shared::cta.b64 [%0], %1;" ::"r"(b), "r"(c)); }
__device__ __forceinline__ void mbar_expect(uint32_t b, uint32_t n) { asm volatile("mbarrier.arrive.expect_tx.shared::cta.b64 _, [%0], %1;" ::"r"(b), "r"(n) : "memory"); }
__device__ __forceinline__ void mbar_arrive(uint32_t b) { asm volatile("mbarrier.arrive.shared::cta.b64 _, [%0];" ::"r"(b) : "memory"); }
__device__ __forceinline__ void mbar_arrive_cl(uint32_t b, uint32_t cta) {
  asm volatile("{\n.reg .b32 ra;\nmapa.shared::cluster.u32 ra, %0, %1;\nmbarrier.arrive.shared::cluster.b64 _, [ra];\n}\n" ::"r"(b), "r"(cta) : "memory");
}
__device__ __forceinline__ void mbar_wait(uint32_t b, uint32_t par) {
  asm volatile("{\n.reg .pred p;\n.reg .u32 c;\nmbarrier.try_wait.parity.shared::cta.b64 p, [%0], %1;\n@p bra D%=;\nmov.u32 c, 0;\n"
               "W%=:\nmbarrier.try_wait.parity.shared::cta.b64 p, [%0], %1;\n@p bra D%=;\n"
               "add.u32 c, c, 1;\nsetp.lt.u32 p, c, 0x40000;\n@p bra W%=;\nD%=:\n}\n" ::"r"(b), "r"(par) : "memory");
}
__device__ __forceinline__ void mbar_wait_lazy(uint32_t b, uint32_t par) {
  asm volatile("{\n.reg .pred p;\n.reg .u32 c;\nmov.u32 c, 0;\nW%=:\nmbarrier.test_wait.parity.shared::cta.b64 p, [%0], %1;\n@p bra D%=;\n"
               "nanosleep.u32 64;\nadd.u32 c, c, 1;\nsetp.lt.u32 p, c, 0x40000;\n@p bra W%=;\nD%=:\n}\n" ::"r"(b), "r"(par) : "memory");
}
__device__ __forceinline__ bool elect() {
  uint32_t p;
  asm volatile("{\n.reg .pred P;\nelect.sync _|P, 0xffffffff;\nselp.u32 %0, 1, 0, P;\n}\n" : "=r"(p));
  return p;
}
__device__ __forceinline__ void bar_sync(int id, int n) { asm volatile("bar.sync %0, %1;" ::"r"(id), "r"(n) : "memory"); }
__device__ __forceinline__ void wg_fence() { asm volatile("wgmma.fence.sync.aligned;" ::: "memory"); }
__device__ __forceinline__ void wg_commit() { asm volatile("wgmma.commit_group.sync.aligned;" ::: "memory"); }
template <int N> __device__ __forceinline__ void wg_wait() { asm volatile("wgmma.wait_group.sync.aligned %0;" ::"n"(N) : "memory"); }
template <int N> __device__ __forceinline__ void pin(float (&d)[N]) {
#pragma unroll
  for (int i = 0; i < N; i++) asm volatile("" : "+f"(d[i])::"memory");
}
template <int N> __device__ __forceinline__ void pin(uint32_t (&d)[N]) {
#pragma unroll
  for (int i = 0; i < N; i++) asm volatile("" : "+r"(d[i])::"memory");
}
__device__ __forceinline__ void fence_async_gl() { asm volatile("fence.proxy.async.global;" ::: "memory"); }
__device__ __forceinline__ void fence_async_smem() { asm volatile("fence.proxy.async.shared::cta;" ::: "memory"); }
__device__ __forceinline__ void bulk_g2s(uint32_t dst, const void* src, uint32_t n, uint32_t bar) {
  asm volatile("cp.async.bulk.shared::cluster.global.mbarrier::complete_tx::bytes [%0], [%1], %2, [%3];" ::"r"(dst), "l"(src), "r"(n), "r"(bar) : "memory");
}
__device__ __forceinline__ void bulk_s2g(void* dst, uint32_t src, uint32_t n) {
  asm volatile("cp.async.bulk.global.shared::cta.bulk_group [%0], [%1], %2;" ::"l"(dst), "r"(src), "r"(n) : "memory");
}
__device__ __forceinline__ void bulk_pf(const void* src, uint32_t n) { asm volatile("cp.async.bulk.prefetch.L2.global [%0], %1;" ::"l"(src), "r"(n) : "memory"); }
__device__ __forceinline__ void tma2(uint32_t dst, const CUtensorMap* m, int c0, int c1, uint32_t bar) {
  asm volatile("cp.async.bulk.tensor.2d.shared::cluster.global.mbarrier::complete_tx::bytes [%0], [%1, {%3, %4}], [%2];" ::"r"(dst), "l"(m), "r"(bar), "r"(c0), "r"(c1) : "memory");
}
__device__ __forceinline__ void tma3(uint32_t dst, const CUtensorMap* m, int c2, uint32_t bar) {
  asm volatile("cp.async.bulk.tensor.3d.shared::cluster.global.mbarrier::complete_tx::bytes [%0], [%1, {%4, %4, %3}], [%2];" ::"r"(dst), "l"(m), "r"(bar), "r"(c2), "r"(0) : "memory");
}
__device__ __forceinline__ void tma2_mc(uint32_t dst, const CUtensorMap* m, int c0, int c1, uint32_t bar) {
  asm volatile("cp.async.bulk.tensor.2d.shared::cluster.global.mbarrier::complete_tx::bytes.multicast::cluster [%0], [%1, {%3, %4}], [%2], %5;"
               ::"r"(dst), "l"(m), "r"(bar), "r"(c0), "r"(c1), "h"((uint16_t)3) : "memory");
}
__device__ __forceinline__ void tma3_mc(uint32_t dst, const CUtensorMap* m, int c1, int c2, uint32_t bar) {
  asm volatile("cp.async.bulk.tensor.3d.shared::cluster.global.mbarrier::complete_tx::bytes.multicast::cluster [%0], [%1, {%5, %3, %4}], [%2], %6;"
               ::"r"(dst), "l"(m), "r"(bar), "r"(c1), "r"(c2), "r"(0), "h"((uint16_t)3) : "memory");
}
__device__ __forceinline__ void tma2_st(const CUtensorMap* m, int c0, int c1, uint32_t src) {
  asm volatile("cp.async.bulk.tensor.2d.global.shared::cta.bulk_group [%0, {%1, %2}], [%3];" ::"l"(m), "r"(c0), "r"(c1), "r"(src) : "memory");
}
__device__ __forceinline__ void bulk_commit() { asm volatile("cp.async.bulk.commit_group;" ::: "memory"); }
__device__ __forceinline__ void bulk_s2g_paced(uint8_t* dst, uint32_t src, uint32_t n, uint32_t piece) {
#pragma unroll 1
  for (uint32_t o = 0; o < n; o += piece) {
    bulk_s2g(dst + o, src + o, min(n - o, piece));
    bulk_commit();
    asm volatile("cp.async.bulk.wait_group.read 0;" ::: "memory");
  }
}
__device__ __forceinline__ void bulk_wait() { asm volatile("cp.async.bulk.wait_group 0;" ::: "memory"); }
__device__ __forceinline__ uint4 ld_b128(const void* p) {
  uint4 v;
  asm volatile("{\n.reg .b64 l, h;\n.reg .b128 t;\nld.relaxed.gpu.global.b128 t, [%4];\nmov.b128 {l, h}, t;\nmov.b64 {%0, %1}, l;\nmov.b64 {%2, %3}, h;\n}\n"
               : "=r"(v.x), "=r"(v.y), "=r"(v.z), "=r"(v.w) : "l"(p) : "memory");
  return v;
}
__device__ __forceinline__ void st_b64(void* p, uint32_t a, uint32_t b) {
  asm volatile("{\n.reg .b64 l;\nmov.b64 l, {%1, %2};\nst.relaxed.gpu.global.b64 [%0], l;\n}\n" ::"l"(p), "r"(a), "r"(b) : "memory");
}
__device__ __forceinline__ uint2 ld_b64(const void* p) {
  uint2 v;
  asm volatile("{\n.reg .b64 l;\nld.relaxed.gpu.global.b64 l, [%2];\nmov.b64 {%0, %1}, l;\n}\n" : "=r"(v.x), "=r"(v.y) : "l"(p) : "memory");
  return v;
}
__device__ __forceinline__ uint32_t ld_rlx(const uint32_t* p) { uint32_t v; asm volatile("ld.relaxed.gpu.global.u32 %0, [%1];" : "=r"(v) : "l"(p) : "memory"); return v; }
__device__ __forceinline__ void red_rlx(uint32_t* p) { asm volatile("red.relaxed.gpu.global.add.u32 [%0], 1;" ::"l"(p) : "memory"); }
__device__ __forceinline__ void poll(const uint32_t* p, uint32_t target) {
  int it = 0;
  while ((int)(ld_rlx(p) - target) < 0 && ++it < SPIN_MAX) __nanosleep(POLL_NS);
  asm volatile("fence.acquire.gpu;" ::: "memory");
}
__device__ __forceinline__ uint4 ldg128v(const void* p) { uint4 v; asm volatile("ld.global.nc.v4.u32 {%0, %1, %2, %3}, [%4];" : "=r"(v.x), "=r"(v.y), "=r"(v.z), "=r"(v.w) : "l"(p)); return v; }
__device__ __forceinline__ uint32_t lds32(uint32_t a) { uint32_t v; asm volatile("ld.shared.u32 %0, [%1];" : "=r"(v) : "r"(a) : "memory"); return v; }
__device__ __forceinline__ uint2 lds64(uint32_t a) { uint2 v; asm volatile("ld.shared.v2.u32 {%0, %1}, [%2];" : "=r"(v.x), "=r"(v.y) : "r"(a) : "memory"); return v; }
__device__ __forceinline__ uint4 lds128(uint32_t a) { uint4 v; asm volatile("ld.shared.v4.u32 {%0, %1, %2, %3}, [%4];" : "=r"(v.x), "=r"(v.y), "=r"(v.z), "=r"(v.w) : "r"(a) : "memory"); return v; }
__device__ __forceinline__ void sts16(uint32_t a, uint32_t v) { asm volatile("st.shared.u16 [%0], %1;" ::"r"(a), "h"((uint16_t)v) : "memory"); }
__device__ __forceinline__ void sts32(uint32_t a, uint32_t v) { asm volatile("st.shared.u32 [%0], %1;" ::"r"(a), "r"(v) : "memory"); }
__device__ __forceinline__ void sts64(uint32_t a, uint32_t x, uint32_t y) { asm volatile("st.shared.v2.u32 [%0], {%1, %2};" ::"r"(a), "r"(x), "r"(y) : "memory"); }
__device__ __forceinline__ void sts128(uint32_t a, uint4 v) { asm volatile("st.shared.v4.u32 [%0], {%1, %2, %3, %4};" ::"r"(a), "r"(v.x), "r"(v.y), "r"(v.z), "r"(v.w) : "memory"); }
__device__ __forceinline__ void stsm4(uint32_t a, uint32_t r0, uint32_t r1, uint32_t r2, uint32_t r3) {
  asm volatile("stmatrix.sync.aligned.m8n8.x4.shared.b16 [%0], {%1, %2, %3, %4};" ::"r"(a), "r"(r0), "r"(r1), "r"(r2), "r"(r3) : "memory");
}
__device__ __forceinline__ void ldsm4(uint32_t a, uint32_t& r0, uint32_t& r1, uint32_t& r2, uint32_t& r3) {
  asm volatile("ldmatrix.sync.aligned.m8n8.x4.shared.b16 {%0, %1, %2, %3}, [%4];" : "=r"(r0), "=r"(r1), "=r"(r2), "=r"(r3) : "r"(a) : "memory");
}
__device__ __forceinline__ void ldsm4t(uint32_t a, uint32_t& r0, uint32_t& r1, uint32_t& r2, uint32_t& r3) {
  asm volatile("ldmatrix.sync.aligned.m8n8.x4.trans.shared.b16 {%0, %1, %2, %3}, [%4];" : "=r"(r0), "=r"(r1), "=r"(r2), "=r"(r3) : "r"(a) : "memory");
}
__device__ __forceinline__ uint32_t pack_bf(float lo, float hi) { uint32_t r; asm("cvt.rn.bf16x2.f32 %0, %1, %2;" : "=r"(r) : "f"(hi), "f"(lo)); return r; }
__device__ __forceinline__ uint32_t pack_h(float lo, float hi) { uint32_t r; asm("cvt.rn.f16x2.f32 %0, %1, %2;" : "=r"(r) : "f"(hi), "f"(lo)); return r; }
__device__ __forceinline__ float bf_lo(uint32_t w) { return __uint_as_float(w << 16); }
__device__ __forceinline__ float bf_hi(uint32_t w) { return __uint_as_float(w & 0xffff0000u); }
__device__ __forceinline__ float bf_round(float v) { return __bfloat162float(__float2bfloat16_rn(v)); }
__device__ __forceinline__ float sqrt_fast(float v) { float r; asm("sqrt.approx.f32 %0, %1;" : "=f"(r) : "f"(v)); return r; }
__device__ __forceinline__ float rcp_fast(float v) { float r; asm("rcp.approx.f32 %0, %1;" : "=f"(r) : "f"(v)); return r; }
__device__ __forceinline__ float tanh_fast(float v) { float r; asm("tanh.approx.f32 %0, %1;" : "=f"(r) : "f"(v)); return r; }

typedef uint32_t h2;
__device__ __forceinline__ __half2 H(h2 v) { return *reinterpret_cast<__half2*>(&v); }
__device__ __forceinline__ h2 U(__half2 v) { return *reinterpret_cast<h2*>(&v); }
__device__ __forceinline__ h2 hadd(h2 a, h2 b) { return U(__hadd2(H(a), H(b))); }
__device__ __forceinline__ h2 hsub(h2 a, h2 b) { return U(__hsub2(H(a), H(b))); }
__device__ __forceinline__ h2 hmul(h2 a, h2 b) { return U(__hmul2(H(a), H(b))); }
__device__ __forceinline__ h2 hfma(h2 a, h2 b, h2 c) { return U(__hfma2(H(a), H(b), H(c))); }
__device__ __forceinline__ h2 hfnma(h2 a, h2 b, h2 c) { return U(__hfma2(__hneg2(H(a)), H(b), H(c))); }
__device__ __forceinline__ h2 hfms(h2 a, h2 b, h2 c) { return U(__hfma2(H(a), H(b), __hneg2(H(c)))); }
__device__ __forceinline__ h2 hneg(h2 a) { return a ^ 0x80008000u; }
constexpr h2 H_TWO = 0x40004000u, H_HALF = 0x38003800u;
constexpr h2 H_C1 = 0x34f234f2u;
constexpr h2 H_C2 = 0xba79ba79u;
constexpr h2 H_S1 = 0x3b9c3b9cu;
constexpr h2 H_S2 = 0x38b438b4u;

__device__ __forceinline__ void dft5(h2 (&r)[5], h2 (&i)[5]) {
  h2 t1r = hadd(r[1], r[4]), t1i = hadd(i[1], i[4]), t2r = hadd(r[2], r[3]), t2i = hadd(i[2], i[3]);
  h2 t3r = hsub(r[1], r[4]), t3i = hsub(i[1], i[4]), t4r = hsub(r[2], r[3]), t4i = hsub(i[2], i[3]);
  h2 a1r = hfma(t2r, H_C2, hfma(t1r, H_C1, r[0])), a1i = hfma(t2i, H_C2, hfma(t1i, H_C1, i[0]));
  h2 a2r = hfma(t2r, H_C1, hfma(t1r, H_C2, r[0])), a2i = hfma(t2i, H_C1, hfma(t1i, H_C2, i[0]));
  h2 b1r = hfma(t4r, H_S2, hmul(t3r, H_S1)), b1i = hfma(t4i, H_S2, hmul(t3i, H_S1));
  h2 b2r = hfnma(t4r, H_S1, hmul(t3r, H_S2)), b2i = hfnma(t4i, H_S1, hmul(t3i, H_S2));
  r[0] = hadd(hadd(r[0], t1r), t2r); i[0] = hadd(hadd(i[0], t1i), t2i);
  r[1] = hadd(a1r, b1i); i[1] = hsub(a1i, b1r);
  r[4] = hsub(a1r, b1i); i[4] = hadd(a1i, b1r);
  r[2] = hadd(a2r, b2i); i[2] = hsub(a2i, b2r);
  r[3] = hsub(a2r, b2i); i[3] = hadd(a2i, b2r);
}
__host__ __device__ constexpr int pfQ(int qi) { return (128 * (qi >> 1) + 5 * (qi & 1)) % 10; }
__host__ __device__ constexpr int pfOFF(int qi) { return (128 * (qi >> 1) + 5 * (qi & 1)) / 10; }

#define PROFARG
#define TS2(i) do { } while (0)
#define TS(i) do { } while (0)

struct Maps {
  CUtensorMap x, w[2][3], wd;
  CUtensorMap ys[2], z, xf, out, wf[2];
};
struct Params {
  const __nv_bfloat16 *x, *wr, *wi, *wg, *wu, *wd;
  __nv_bfloat16* out;
  uint8_t* scr;
  const uint32_t* tab;
};
#define cnt(i) (reinterpret_cast<uint32_t*>(p.scr + G_CNT) + (i) * 32)
#define g_stats reinterpret_cast<uint2*>(p.scr + G_STATS)
#define g_eb reinterpret_cast<uint4*>(p.scr + G_EB)
#define g_Y (p.scr + G_Y)
#define g_Z (p.scr + G_Z)
#define g_h (p.scr + G_H)
#define cF p.tab
#define cM (p.tab + 2048)
#define cG (p.tab + 4096)
#define cT (p.tab + 6144)

struct Ring { uint32_t st, fb, ph; };
__device__ __forceinline__ void ring_next(Ring& r, uint32_t sb) {
  r.st += STG_B; r.fb += 8;
  if (r.st == sb + NSTG * STG_B) { r.st = sb; r.fb -= 8 * NSTG; r.ph ^= 1; }
}
__device__ __forceinline__ void ring_release(uint32_t fb, int tid) {
  if (tid < 2) mbar_arrive_cl(fb + 8 * B_EMPTY, tid);
}
__device__ __forceinline__ void g2_first(uint32_t bar, int i) {
  if (i < 6 && i != 3) mbar_wait(bar + 8 * (B_EMPTY + i - (i > 3)), 1);
  if (i == 8) mbar_wait(bar + 8 * B_H2F, 0);
}
__device__ __forceinline__ void center(uint32_t (&a)[4], uint32_t m0, uint32_t m1) {
#pragma unroll
  for (int i = 0; i < 4; i++) asm("sub.rn.bf16x2 %0, %0, %1;" : "+r"(a[i]) : "r"((i & 1) ? m1 : m0));
}
template <int N>
__device__ __forceinline__ void gemm1_tile(float (&ag)[56], float (&au)[56], Ring& r, uint32_t sb, int v, int tid, uint32_t m0, uint32_t m1
) {
  const uint32_t arow = ((tid >> 5) * 16 + (tid & 15)) * 128, asw = ((tid >> 4) & 1) ^ (tid & 7);
  uint32_t p1 = 0, a0[4], a1[4], a2[4], a3[4];
#pragma unroll 1
  for (int kp = 0; kp < 10; kp++) {
    const Ring r0 = r;
    ring_next(r, sb);
    const uint32_t a = (v ? r.st : r0.st) + arow, b0 = dlo(r0.st + 8192, 4096), b1 = dlo(r.st + 8192, 4096);
    mbar_wait(r0.fb, r0.ph);
    if (v) mbar_wait(r.fb, r.ph);
    if (tid == 0 && v == 0) TS2((N == 112 ? 0 : 10) + kp);
    ldsm4(a + (asw << 4), a0[0], a0[1], a0[2], a0[3]);
    ldsm4(a + ((asw ^ 2) << 4), a1[0], a1[1], a1[2], a1[3]);
    center(a0, m0, m1); center(a1, m0, m1);
    wg_fence();
    mma_g1<N>(ag, a0, b0, kp);
    mma_g1<N>(au, a0, b0 + 512, kp);
    mma_g1<N>(ag, a1, b0 + 128, 1);
    mma_g1<N>(au, a1, b0 + 640, 1);
    wg_commit();
    wg_wait<1>();
    pin(a2); pin(a3);
    if (kp > 0) ring_release(p1, tid);
    ldsm4(a + ((asw ^ 4) << 4), a2[0], a2[1], a2[2], a2[3]);
    ldsm4(a + ((asw ^ 6) << 4), a3[0], a3[1], a3[2], a3[3]);
    center(a2, m0, m1); center(a3, m0, m1);
    if (!v) mbar_wait(r.fb, r.ph);
    wg_fence();
    mma_g1<N>(ag, a2, b1, 1);
    mma_g1<N>(au, a2, b1 + 512, 1);
    mma_g1<N>(ag, a3, b1 + 128, 1);
    mma_g1<N>(au, a3, b1 + 640, 1);
    wg_commit();
    wg_wait<1>();
    pin(a0); pin(a1);
    ring_release(r0.fb, tid);
    p1 = r.fb;
    ring_next(r, sb);
  }
  wg_wait<0>();
  ring_release(p1, tid);
}

__device__ __forceinline__ void glu_group(const float* ag, const float* au, float rh0, float rh1, uint32_t& w0, uint32_t& w1) {
  const float t00 = tanh_fast(ag[0] * rh0), t01 = tanh_fast(ag[1] * rh0), t10 = tanh_fast(ag[2] * rh1), t11 = tanh_fast(ag[3] * rh1);
  w0 = pack_bf(fmaf(t00, au[0], au[0]), fmaf(t01, au[1], au[1]));
  w1 = pack_bf(fmaf(t10, au[2], au[2]), fmaf(t11, au[3], au[3]));
}

__device__ __forceinline__ uint32_t eb_max(uint32_t sb, int lane) {
  uint32_t e4 = lds32(sb + O_EB + lane * 4);
  e4 = __vmaxu4(e4, e4 >> 16);
  return __reduce_max_sync(0xffffffffu, max(e4 & 0xffu, (e4 >> 8) & 0xffu));
}

struct ColTw { h2 tw[16], wr, wi; };
__device__ __forceinline__ void column_tw(ColTw& T, const uint32_t* tab, int tid) {
  const uint4* tp = reinterpret_cast<const uint4*>(tab) + tid;
#pragma unroll
  for (int j = 0; j < 4; j++) { const uint4 q = ldg128v(tp + j * 128); T.tw[4 * j] = q.x; T.tw[4 * j + 1] = q.y; T.tw[4 * j + 2] = q.z; T.tw[4 * j + 3] = q.w; }
  const uint4 q = ldg128v(tp + 4 * 128); T.wr = q.x; T.wi = q.y;
}
__device__ __forceinline__ void column_one(uint32_t sb, int tid, uint32_t db, uint32_t tb, const ColTw& T, const h2 (&fac)[4]) {
  const int w = tid >> 5, lane = tid & 31, g = lane >> 2, t = lane & 3;
  const h2 (&tw)[16] = T.tw;
  const h2 wr = T.wr, wi = T.wi;
  const uint32_t m = dlo(sb + O_M, 1024), b = dlo(db, 16);
  const uint32_t sofs = (16 * w + (lane & 15)) * 128 + ((((lane >> 4) ^ lane) & 7) << 4);
  h2 d[16], e[16];
  {
    h2 c[32];
    wg_fence();
#pragma unroll
    for (int k = 0; k < 2; k++) mma_h128n(c, dlo(sb + O_M, 2048) + 256 * k, HI_0A, dlo(db, 2048) + 64 * k, HI_64, k);
    wg_commit();
    wg_wait<0>();
    pin(c);
#pragma unroll
    for (int j = 0; j < 8; j++) {
      const int i = 8 * (j >> 1) + 2 * (j & 1);
      d[2 * j] = hsub(c[i], c[i + 5]);
      d[2 * j + 1] = hadd(c[i + 4], c[i + 1]);
    }
  }
#pragma unroll
  for (int j = 0; j < 4; j++) {
    const h2 ar = d[2 * j], ai = d[2 * j + 1], br = d[2 * j + 8], bi = d[2 * j + 9];
    const h2 pr = hfnma(wi, bi, hfma(wr, br, ar)), pi = hfma(wi, br, hfma(wr, bi, ai));
    const h2 qr = hfms(ar, H_TWO, pr), qi = hfms(ai, H_TWO, pi);
    e[4 * j + 0] = hfnma(pi, tw[4 * j + 1], hmul(pr, tw[4 * j]));
    e[4 * j + 2] = hfma(pi, tw[4 * j], hmul(pr, tw[4 * j + 1]));
    e[4 * j + 1] = hfnma(qi, tw[4 * j + 3], hmul(qr, tw[4 * j + 2]));
    e[4 * j + 3] = hfma(qi, tw[4 * j + 2], hmul(qr, tw[4 * j + 3]));
  }
  wg_fence();
#pragma unroll
  for (int k = 0; k < 4; k++) mma_h64r(d, e[4 * k], e[4 * k + 1], e[4 * k + 2], e[4 * k + 3], m + 128 * k, HI_0A, k);
  wg_commit();
  h2 W[16];
#pragma unroll
  for (int i = 0; i < 8; i++) {
    const uint2 q = lds64(tb + w * 256 + t * 64 + g * 8 + i * 1024);
    const h2 f = __byte_perm(fac[i >> 1], 0, (i & 1) ? 0x3232 : 0x1010);
    W[2 * i] = hmul(q.x, f); W[2 * i + 1] = hmul(q.y, f);
  }
  wg_wait<0>();
  pin(d); pin(e);
#pragma unroll
  for (int i = 0; i < 4; i++)
#pragma unroll
    for (int r = 0; r < 2; r++) {
      const h2 xr = d[4 * i + r], xi = d[4 * i + 2 + r], fr = W[4 * i + 2 * r], fi = W[4 * i + 2 * r + 1];
      e[4 * i + r] = hfnma(xi, fi, hmul(xr, fr));
      e[4 * i + 2 + r] = hfnma(xr, fi, hmul(hneg(xi), fr));
    }
  wg_fence();
#pragma unroll
  for (int k = 0; k < 4; k++) mma_h64r(d, e[4 * k], e[4 * k + 1], e[4 * k + 2], e[4 * k + 3], m + 128 * k, HI_0A, k);
  wg_commit();
  bar_sync(1, 128);
  wg_wait<0>();
  pin(d); pin(e);
#pragma unroll
  for (int i = 0; i < 4; i++) {
    const h2 ur = d[4 * i], vr = d[4 * i + 1], ui = d[4 * i + 2], vi = d[4 * i + 3];
    const h2 pr = hfnma(ui, tw[4 * i + 1], hmul(ur, tw[4 * i])), pi = hfma(ui, tw[4 * i], hmul(ur, tw[4 * i + 1]));
    const h2 ar = hfnma(vi, tw[4 * i + 3], hfma(vr, tw[4 * i + 2], pr)), ai = hfma(vi, tw[4 * i + 2], hfma(vr, tw[4 * i + 3], pi));
    const h2 dr = hfms(pr, H_TWO, ar), di = hfms(pi, H_TWO, ai);
    e[2 * i] = ar; e[2 * i + 1] = ai;
    e[2 * i + 8] = hfnma(di, wi, hmul(dr, wr));
    e[2 * i + 9] = hfma(di, wr, hmul(dr, wi));
  }
#pragma unroll
  for (int j = 0; j < 8; j += 2) stsm4(db + (sofs ^ (j << 4)), e[2 * j], e[2 * j + 1], e[2 * j + 2], e[2 * j + 3]);
  bar_sync(1, 128);
  fence_async_smem();
  wg_fence();
#pragma unroll
  for (int k = 0; k < 4; k++) mma_h64n(d, m + 128 * k, HI_0A, b + 128 * k, HI_128, k);
  wg_commit();
  wg_wait<0>();
  pin(d);
#pragma unroll
  for (int j = 0; j < 8; j += 2)
    stsm4(tb + j * 1024 + (8 * w + (lane & 7)) * 64 + (((((lane >> 2) & 2) | (lane >> 4)) ^ ((lane >> 1) & 3)) << 4), d[2 * j], d[2 * j + 1], d[2 * j + 2], d[2 * j + 3]);
}

__device__ __forceinline__ void inverse_rows(uint32_t sb, int tid, int v, int slab, const uint4 tq0, const uint4 tq1) {
  const int w = tid >> 5, lane = tid & 31, g = lane >> 2, t = lane & 3;
  const uint32_t sc2 = ((eb_max(sb, lane) + 1) << 7) * 0x10001u;
  const h2 wr = tq0.x, wi = tq0.y;
  const uint32_t cidx[5] = {tq0.z, tq0.w, tq1.x, tq1.y, tq1.z};
  const bool spec = tid < 4;
  h2 pr[5], pi[5], qr[5], qi_[5];
  const uint32_t zb = (sb + O_DATA + v * 16 + t * 4) ^ ((slab & 24) << 1);
#pragma unroll
  for (int j = 0; j < 5; j++) {
    const uint32_t z0 = (zb + (cidx[j] & 0x7fffu) * 64) ^ ((cidx[j] & 6) << 3), z1 = (zb + ((cidx[j] >> 16) & 0x7fffu) * 64) ^ ((cidx[j] >> 13) & 48);
    pr[j] = lds32(z0);
    pi[j] = lds32((j == 0 && spec) ? zb + 320 * 64 : z0 ^ 32) ^ ((cidx[j] & 0x8000u) ? 0x80008000u : 0u);
    qr[j] = lds32(z1);
    qi_[j] = lds32(z1 ^ 32) ^ ((cidx[j] & 0x80000000u) ? 0x80008000u : 0u);
  }
  if (spec) {
    const h2 r1 = pr[1], i1 = pi[1], r4 = pr[4], i4 = pi[4], r2 = pr[2], i2 = pi[2], r3 = pr[3], i3 = pi[3];
    pr[1] = hadd(r1, i4); pi[1] = hadd(i1, r4);
    pr[4] = hsub(r1, i4); pi[4] = hsub(r4, i1);
    pr[2] = hsub(r2, i3); pi[2] = hsub(r3, i2);
    pr[3] = hadd(r2, i3); pi[3] = hadd(i2, r3);
  }
  dft5(pr, pi);
  dft5(qr, qi_);
  const uint32_t tb = sb + O_T + v * 10240, ta = tb + (8 * w + g) * 16 + t * 4;
#pragma unroll
  for (int a5 = 0; a5 < 5; a5++) {
    const h2 dr = hsub(pr[a5], qr[a5]), di = hsub(pi[a5], qi_[a5]);
    h2 ar = hadd(pr[a5], qr[a5]), ai = hadd(pi[a5], qi_[a5]);
    h2 br = hfnma(di, wi, hmul(dr, wr)), bi = hfma(di, wr, hmul(dr, wi));
    if (spec) { ar = hadd(pr[a5], pi[a5]); ai = hadd(qr[a5], qr[a5]); br = hsub(pr[a5], pi[a5]); bi = hadd(qi_[a5], qi_[a5]); }
    sts32(ta + a5 * 2048, ar); sts32(ta + a5 * 2048 + 512, ai);
    sts32(ta + a5 * 2048 + 1024, br); sts32(ta + a5 * 2048 + 1536, bi);
  }
  bar_sync(4 + v, 128);
  fence_async_smem();
  float o[40];
  mbar_wait(sb + O_BAR + 8 * B_CONST, 1);
  const uint32_t a = dlo(sb + O_CONST, 16), b = dlo(tb, 128);
  wg_fence();
#pragma unroll
  for (int k = 0; k < 4; k++) mma_hf80n(o, a + 2 * k, HI_128, b + 16 * k, HI_0K, k);
  wg_commit();
  wg_wait<0>();
  pin(o);
  const __nv_bfloat162 sc = *reinterpret_cast<const __nv_bfloat162*>(&sc2);
  const int brow = 16 * w + (lane & 15);
#pragma unroll
  for (int qi = 0; qi < 10; qi += 2) {
    uint32_t u[4];
#pragma unroll
    for (int i = 0; i < 4; i++) {
      u[i] = pack_bf(o[4 * qi + 2 * i], o[4 * qi + 2 * i + 1]);
      const __nv_bfloat162 mm = __hmul2(*reinterpret_cast<__nv_bfloat162*>(&u[i]), sc);
      u[i] = *reinterpret_cast<const uint32_t*>(&mm);
    }
    const int q = lane & 16 ? pfQ(qi + 1) : pfQ(qi), off = lane & 16 ? pfOFF(qi + 1) : pfOFF(qi);
    const int d = q + 10 * ((brow + off) & 63);
    stsm4(sb + O_S + d * 32 + ((v * 16) ^ ((d & 4) << 2)), u[0], u[1], u[2], u[3]);
  }
}

template <int NW>
__device__ __forceinline__ void filter_convert(uint32_t sb, int w, int lane, int barid
) {
  constexpr int NI = (40 + NW) / NW;
  uint32_t u[NI][4], mx = 0;
  mbar_wait(sb + O_BAR + 8 * B_WSLAB, 0);
#pragma unroll
  for (int i = 0; i < NI; i++) ldsm4(sb + O_TEMP + lane * 656 + min(w + NW * i, 40) * 16, u[i][0], u[i][1], u[i][2], u[i][3]);
#pragma unroll
  for (int i = 0; i < NI; i++)
    mx = __vmaxu2(__vmaxu2(mx, u[i][0] & 0x7fff7fffu), __vmaxu2(__vmaxu2(u[i][1] & 0x7fff7fffu, u[i][2] & 0x7fff7fffu), u[i][3] & 0x7fff7fffu));
  mx = __reduce_max_sync(0xffffffffu, max(mx & 0xffffu, mx >> 16));
  if (lane == 0) asm volatile("red.shared.max.u32 [%0], %1;" ::"r"(sb + O_WMAX), "r"(mx) : "memory");
  bar_sync(barid, NW * 32);
  const uint32_t ef = min(max(lds32(sb + O_WMAX) >> 7, 1u), 252u), sc2 = ((253u - ef) << 7) * 0x10001u;
  const __nv_bfloat162 sc = *reinterpret_cast<const __nv_bfloat162*>(&sc2);
  if (w == 0 && lane == 0) { sts32(sb + O_TEMP + 336 * 64, ef); TS(5); }
  const int k0 = 8 * w + 2 * (lane & 3) - (lane >> 2);
  const uint32_t a0 = (sb + O_TEMP + k0 * 64 + (lane >> 2) * 8) ^ ((k0 & 6) << 3), b0 = ~((~lane >> 2) & 1);
  const uint32_t a1 = (sb + O_TEMP + (k0 + 1) * 64 + (lane >> 2) * 8) ^ (((k0 + 1) & 6) << 3);
#pragma unroll
  for (int i = 0; i < NI; i++) {
#pragma unroll
    for (int j = 0; j < 4; j++) {
      const __nv_bfloat162 m = __hmul2(*reinterpret_cast<__nv_bfloat162*>(&u[i][j]), sc);
      u[i][j] = *reinterpret_cast<const uint32_t*>(&m);
    }
    const uint32_t k = k0 + 8 * NW * i;
    const bool edge = i == 0 || i >= NI - 2;
    if (!edge || (k <= 320 && (i < NI - 1 || w == 0)))
      sts64(a0 + i * NW * 512, pack_h(bf_lo(u[i][0]), bf_lo(u[i][1])) & b0, pack_h(bf_lo(u[i][2]), bf_lo(u[i][3])));
    if (!edge || (k + 1 <= 320 && (i < NI - 1 || w == 0)))
      sts64(a1 + i * NW * 512, pack_h(bf_hi(u[i][0]), bf_hi(u[i][1])) & b0, pack_h(bf_hi(u[i][2]), bf_hi(u[i][3])));
  }
  __syncwarp();
  if (lane == 0) mbar_arrive(sb + O_BAR + 8 * B_WS);
  if (w == 0 && lane == 0) TS(4);
}

template <int C, int N>
__device__ __forceinline__ void sts_words(uint32_t rowx, uint32_t seg16, uint32_t imm, const uint32_t* wd) {
  if constexpr (N > 0) {
    constexpr int r = ((C % 4) + 4) % 4;
    const uint32_t a = (((seg16 + 4 * C) & 127) ^ rowx) + imm;
    if constexpr (r == 0 && N == 4) sts128(a, make_uint4(wd[0], wd[1], wd[2], wd[3]));
    else if constexpr ((r & 1) == 0 && N >= 2) { sts64(a, wd[0], wd[1]); sts_words<C + 2, N - 2>(rowx, seg16, imm, wd + 2); }
    else { sts32(a, wd[0]); sts_words<C + 1, N - 1>(rowx, seg16, imm, wd + 1); }
  }
}
template <int QI>
__device__ __forceinline__ void ln_scatter(const uint32_t (&xw)[40], float rs, float nb, uint32_t rowx, uint32_t seg16) {
  constexpr int q = pfQ(QI), off = pfOFF(QI);
  float e[8];
#pragma unroll
  for (int i = 0; i < 8; i++) e[i] = fmaf((q & 1) ? bf_hi(xw[(q + 10 * i) >> 1]) : bf_lo(xw[(q + 10 * i) >> 1]), rs, nb);
  if constexpr ((off & 1) == 0) {
    const uint32_t wd[4] = {pack_h(e[0], e[1]), pack_h(e[2], e[3]), pack_h(e[4], e[5]), pack_h(e[6], e[7])};
    sts_words<128 - off / 2, 4>(rowx, seg16, QI * 2048, wd);
  } else {
    const uint32_t wd[3] = {pack_h(e[1], e[2]), pack_h(e[3], e[4]), pack_h(e[5], e[6])}, ends = pack_h(e[7], e[0]);
    constexpr int C = 128 - (off + 1) / 2;
    sts16((((seg16 + 4 * C) & 127) ^ rowx) + QI * 2048 + 2, ends >> 16);
    sts_words<C + 1, 3>(rowx, seg16, QI * 2048, wd);
    sts16((((seg16 + 4 * (C + 4)) & 127) ^ rowx) + QI * 2048, ends);
  }
  if constexpr (QI < 9) ln_scatter<QI + 1>(xw, rs, nb, rowx, seg16);
}

__global__ void __cluster_dims__(2, 1, 1) __launch_bounds__(512, 1)
fused_kernel(const Params p, const __grid_constant__ Maps mp) {
  extern __shared__ __align__(1024) uint8_t smem_raw[];
  uint32_t sb;
  asm volatile("{\n.reg .u64 t;\ncvta.to.shared.u64 t, %1;\ncvt.u32.u64 %0, t;\n}\n" : "=r"(sb) : "l"(smem_raw));
  const int warp = __shfl_sync(0xffffffffu, threadIdx.x >> 5, 0);
  const int wgi = warp >> 2;
  int tid = threadIdx.x & 127;
  asm volatile("" : "+r"(tid));
  const int bid = blockIdx.x, rank = bid & 1, slot = (bid >> 1) & 7, rb = 2 * (bid >> 4) + rank;
  const int kap = slot >> 2, cn = slot & 3;
  const int slab = rb * 8 + slot;
  const uint32_t bar = sb + O_BAR;
  uint32_t ep0 = 0;
  if (threadIdx.x == 32) ep0 = ld_rlx(cnt(C_EPOCH));
  if (warp < 4 && elect()) {
    if (warp & 2) {
      if (warp & 1) {
        asm volatile("prefetch.tensormap [%0];" ::"l"(&mp.x) : "memory");
        asm volatile("prefetch.tensormap [%0];" ::"l"(&mp.w[rank][0]) : "memory");
        asm volatile("prefetch.tensormap [%0];" ::"l"(&mp.w[rank][1]) : "memory");
      } else {
        mbar_init(bar + 8 * B_CONST, 1);
        mbar_expect(bar + 8 * B_CONST, 8192 + 20480);
        bulk_g2s(sb + O_DATA, p.x + (size_t)slab * 16 * 640, 20480, bar + 8 * B_CONST);
        bulk_g2s(sb + O_CONST, cF, 8192, bar + 8 * B_CONST);
        if (bid < 7) bulk_pf(cT + bid * 512, 2048);
#pragma unroll
        for (int l = B_CONST + 1; l < B_NUM; l++) mbar_init(bar + 8 * l, bar_count(l));
        sts32(sb + O_WMAX, 0);
      }
    } else if (warp & 1) {
#pragma unroll
      for (int l = 16; l < 32; l++) mbar_init(bar + 8 * l, bar_count(l));
    } else {
#pragma unroll
      for (int l = 0; l < 16; l++) mbar_init(bar + 8 * l, bar_count(l));
    }
    asm volatile("fence.mbarrier_init.release.cluster;" ::: "memory");
  }
  __syncwarp();
  asm volatile("barrier.cluster.arrive.relaxed.aligned;" ::: "memory");
  if (warp < 4) {
    asm volatile("setmaxnreg.dec.sync.aligned.u32 %0;" ::"n"(R_CHORE));
    if (warp == 0) {
      asm volatile("barrier.cluster.wait.acquire.aligned;" ::: "memory");
      if (elect()) {
        const CUtensorMap* mw = &mp.w[rank][0];
        const uint32_t bo = 8192 + rank * 8192;
        const int xr = rb * 128;
#pragma unroll 1
        for (int tile = 0; tile < 2; tile++) {
          const int f0 = 864 * kap + (tile ? 448 + 104 * cn : 112 * cn);
          const CUtensorMap* mw1 = mw + 1 + tile;
          const uint32_t bytes = tile ? 8192 + 64 * 208 : 8192 + 64 * 224;
          uint32_t st = sb + 6 * tile * STG_B, fb = bar + 48 * tile, ph = 1;
          int kk = 0;
#pragma unroll 1
          for (int i = 0; i < 10; i++) {
#pragma unroll
            for (int h = 0; h < 2; h++) {
              mbar_wait(fb + 8 * B_EMPTY, ph);
              mbar_expect(fb, bytes);
              tma2(st, &mp.x, kk, xr + 64 * h, fb);
              tma2_mc(st + bo, mw, f0, kk + 32 * h, fb);
              tma2_mc(st + bo + 4096, mw1, f0 + 64, kk + 32 * h, fb);
              st += STG_B; fb += 8;
              if (fb == bar + 56) { st = sb; fb = bar; ph ^= 1; }
            }
            kk += 64;
          }
          TS(tile ? 29 : 60);
        }
        mbar_arrive(bar + 8 * B_G2GO);
        TS(1);
        int k0 = 864 * kap + 16 * rank;
#pragma unroll 1
        for (int lap = 0; lap < 3; lap++) {
#pragma unroll
          for (int i = 0; i < 9; i++) {
            const uint32_t fb = bar + 8 * (B_G2 + i);
            if (lap == 0) g2_first(bar, i); else mbar_wait(fb + 8 * B_EMPTY, lap - 1);
            mbar_expect(fb, 18432);
            tma3_mc(sb + i * STG2_B + 8192 + rank * 5120, &mp.wd, k0 + 32 * i, cn * 5, fb);
          }
          k0 += 288;
        }
      }
    } else {
      const int ct = threadIdx.x - 32;
      if (sb & 1023) __trap();
      asm volatile("barrier.cluster.wait.acquire.aligned;" ::: "memory");
      if (ct < 32) {
        if (ct == 0) { sts32(sb + O_EPOCH, ep0); mbar_arrive(bar + 8 * B_EPOCH); TS(9); }
        __syncwarp();
        if (elect()) {
#pragma unroll 1
          for (int tile = 0; tile < 2; tile++) {
            const uint32_t src = sb + (tile ? O_H2 : O_CONST), n = tile ? 13312 : 14336;
            uint8_t* dst = g_h + (size_t)(rb * 432 + kap * 108 + (tile ? 56 + 13 * cn : 14 * cn)) * 1024;
            mbar_wait(bar + 8 * B_HD, tile);
            fence_async_smem();
            bulk_s2g_paced(dst, src, 4096, 4096);
            if (tile) {
              mbar_arrive_cl(bar + 8 * B_H2F, 0);
              mbar_arrive_cl(bar + 8 * B_H2F, 1);
            }
            bulk_s2g_paced(dst + 4096, src + 4096, n - 4096, tile ? PIECE2 : PIECE);
            bulk_s2g_paced(dst + 216 * 1024, src + n, n, tile ? PIECE2 : PIECE);
            mbar_arrive(bar + 8 * B_HF);
            bulk_wait();
            red_rlx(cnt(C_H + (rb * 2 + kap) * 2 + tile));
            TS(6 + 6 * tile);
          }
        }
      } else if (ct >= 64) {
        if (elect()) {
          mbar_wait_lazy(bar + 8 * 6, 0);
#pragma unroll 1
          for (int i = 0; i < 20; i++) {
            bulk_pf(((i & 1) ? p.wu : p.wg) + (size_t)(bid * 5 + (i >> 2)) * 1728 + 448 + (i & 2) * 432, 832);
            if ((i & 3) == 3) __nanosleep(PF_NS);
          }
#pragma unroll 1
          for (int i = 0; i < 4; i++) { bulk_pf(reinterpret_cast<const uint8_t*>(p.wd) + bid * 17280 + i * 4320, 4320); __nanosleep(PF_NS); }
          mbar_wait_lazy(bar + 8 * B_TD, 0);
          const uint32_t ep = lds32(sb + O_EPOCH) + 1;
          const uint8_t* hsrc = g_h + (size_t)(rb * 432 + kap * 108) * 1024;
          poll(cnt(C_H + (rb * 2 + kap) * 2), ep * 4);
          fence_async_gl();
          mbar_wait_lazy(bar + 8 * B_G2GO, 0);
          uint32_t seen = 0;
#pragma unroll 1
          for (int lap = 0; lap < 3; lap++) {
#pragma unroll
            for (int i = 0; i < 9; i++) {
              const uint32_t fb = bar + 8 * (B_G2 + i);
              if (i == 2 && lap == 1) seen = ld_rlx(cnt(C_H + (rb * 2 + kap) * 2 + 1));
              if (i == 5 && lap == 1) {
                if ((int)(seen - ep * 4) < 0) poll(cnt(C_H + (rb * 2 + kap) * 2 + 1), ep * 4);
                asm volatile("fence.acquire.gpu;" ::: "memory");
                fence_async_gl();
              }
              if (lap == 0) g2_first(bar, i); else mbar_wait(fb + 8 * B_EMPTY, lap - 1);
              bulk_g2s(sb + i * STG2_B, hsrc + i * 4096, 4096, fb);
              bulk_g2s(sb + i * STG2_B + 4096, hsrc + 216 * 1024 + i * 4096, 4096, fb);
            }
            hsrc += 9 * 4096;
          }
          mbar_arrive(bar + 8 * B_LAST);
        }
      } else {
        const int nc = bid < 65 ? 3 : 2, col0 = bid < 65 ? 3 * bid : 2 * bid + 65;
        const int piece = ((slab & 3) * 32 + (slab >> 2)) * 32;
        const bool lead = elect();
        if (lead) {
          if (WS_NS) __nanosleep(WS_NS);
          const int f8 = ((bid >> 2) & 3) + 4 * ((bid >> 4) & 1) + 8 * (8 * (bid >> 5) + 2 * (bid & 3));
          mbar_expect(bar + 8 * B_WSLAB, 32 * 656);
#pragma unroll
          for (int i = 0; i < 4; i++) tma3(sb + O_TEMP + i * 5248, &mp.wf[i >> 1], f8 + 8 * (i & 1), bar + 8 * B_WSLAB);
          mbar_wait_lazy(bar + 8 * B_YS, 0);
          fence_async_smem();
#pragma unroll 1
          for (int i = 0; i < 12; i++) {
            if (i == 6) {
              mbar_wait_lazy(bar + 8 * B_WS, 0);
              fence_async_smem();
              TS(7);
              bulk_s2g(g_eb + (bid & 15) * 8 + (bid >> 4), sb + O_TEMP + 336 * 64, 16);
            }
            if (i < 6) tma2_st(&mp.ys[0], piece, 56 * i, sb + O_DATA + i * 3584);
            else tma2_st(&mp.ys[1], bid * 32, 56 * (i - 6), sb + O_TEMP + (i - 6) * 3584);
            bulk_commit();
            asm volatile("cp.async.bulk.wait_group.read 0;" ::: "memory");
            if (ST_NS) __nanosleep(ST_NS);
          }
          bulk_wait();
          red_rlx(cnt(C_Y));
          mbar_arrive(bar + 8 * B_DF);
          TS(8);
          mbar_expect(bar + 8 * B_COL0, 3 * 8192);
          bulk_g2s(sb + O_M, cM, 8192, bar + 8 * B_COL0);
          poll(cnt(C_Y), (lds32(sb + O_EPOCH) + 1) * 128);
          fence_async_gl();
          TS(21);
          bulk_g2s(sb + col_y(0), g_Y + (size_t)col0 * 8192, 8192, bar + 8 * B_COL0);
          bulk_g2s(sb + col_w(0), g_Y + (size_t)(321 + col0) * 8192, 8192, bar + 8 * B_COL0);
        }
        __syncwarp();
        {
          const int l = ct - 32;
          const uint32_t e0 = __ldcg(&g_eb[4 * l].x), e1 = __ldcg(&g_eb[4 * l + 1].x), e2 = __ldcg(&g_eb[4 * l + 2].x), e3 = __ldcg(&g_eb[4 * l + 3].x);
          sts32(sb + O_EB + l * 4, e0 | (e1 << 8) | (e2 << 16) | (e3 << 24));
          __syncwarp();
        }
        if (lead) {
          const uint32_t ep = lds32(sb + O_EPOCH) + 1;
          mbar_arrive(bar + 8 * B_COL0);
          if (bid == 0) *cnt(C_EPOCH) = ep;
          mbar_wait_lazy(bar + 8 * B_HF, 0);
          mbar_expect(bar + 8 * B_COL1, (nc - 1) * 16384);
#pragma unroll 1
          for (int i = 2; i < 2 * nc; i++) {
            bulk_g2s(sb + (i == 2 ? col_y(1) : i == 3 ? col_w(1) : i == 4 ? col_y(2) : col_w(2)), g_Y + (size_t)((i & 1) * 321 + col0 + (i >> 1)) * 8192, 8192,
                     bar + 8 * B_COL1);
            __nanosleep(LD_NS);
          }
#pragma unroll 1
          for (int c = 0; c < nc; c++) {
            mbar_wait_lazy(bar + 8 * (B_ZD + c), 0);
            fence_async_smem();
            bulk_s2g_paced(g_Z + (size_t)(col0 + c) * 8192, sb + (c == 0 ? col_w(0) : c == 1 ? col_w(1) : col_w(2)), 8192, PIECE);
            if (c == 0) mbar_arrive(bar + 8 * B_Z0F);
          }
          TS(62);
          bulk_wait();
          red_rlx(cnt(C_Z));
          mbar_expect(bar + 8 * B_CONST, 8192);
          bulk_g2s(sb + O_CONST, cG, 8192, bar + 8 * B_CONST);
          TS(23);
          poll(cnt(C_Z), ep * 128);
          fence_async_gl();
          TS(24);
          mbar_wait_lazy(bar + 8 * B_LAST, 0);
          mbar_expect(bar + 8 * B_ZIN, 6 * 3584);
#pragma unroll 1
          for (int i = 0; i < 6; i++) tma2(sb + O_DATA + i * 3584, &mp.z, piece, 56 * i, bar + 8 * B_ZIN);
          mbar_wait(bar + 8 * B_HF, 1);
          mbar_expect(bar + 8 * B_X, 20480);
#pragma unroll 1
          for (int i = 0; i < 8; i++) tma2(sb + O_TEMP + i * 2560, &mp.xf, 80 * i, slab * 16, bar + 8 * B_X);
        }
      }
    }
  } else if (!(warp & 8)) {
    if (R_AUX > 128) asm volatile("setmaxnreg.inc.sync.aligned.u32 %0;" ::"n"(R_AUX));
    else asm volatile("setmaxnreg.dec.sync.aligned.u32 %0;" ::"n"(R_AUX));
    const int w = tid >> 5, lane = tid & 31, t = lane & 3;
    uint32_t ep;
    uint4 tq0, tq1;
    asm volatile("barrier.cluster.wait.acquire.aligned;" ::: "memory");
    {
      uint32_t xw[40];
      float mb, rs;
      {
        mbar_wait(bar + 8 * B_CONST, 0);
#pragma unroll
      for (int j = 0; j < 10; j++) { const uint4 q = lds128(sb + O_DATA + tid * 160 + j * 16); xw[4 * j] = q.x; xw[4 * j + 1] = q.y; xw[4 * j + 2] = q.z; xw[4 * j + 3] = q.w; }
      float s0 = 0.f, s1 = 0.f, q0 = 0.f, q1 = 0.f;
#pragma unroll
      for (int j = 0; j < 40; j++) {
        const float a = bf_lo(xw[j]), b = bf_hi(xw[j]);
        s0 += a; q0 = fmaf(a, a, q0); s1 += b; q1 = fmaf(b, b, q1);
      }
      s0 += s1; q0 += q1;
#pragma unroll
      for (int o = 1; o < 8; o <<= 1) { s0 += __shfl_xor_sync(0xffffffffu, s0, o); q0 += __shfl_xor_sync(0xffffffffu, q0, o); }
      const float mean = s0 * (1.f / 640.f), var = fmaxf(fmaf(-mean, mean, q0 * (1.f / 640.f)), 0.f);
      mb = bf_round(mean); rs = rcp_fast(bf_round(sqrt_fast(bf_round(bf_round(var) + 1e-5f))));
      }
      mbar_wait(bar + 8 * B_EPOCH, 0);
      ep = lds32(sb + O_EPOCH) + 1;
      if ((lane & 7) == 0) {
        st_b64(g_stats + slab * 16 + w * 4 + (lane >> 3), __float_as_uint(mb) | (ep & 0xffff), __float_as_uint(rs));
        sts32(sb + O_RQ + (w * 4 + (lane >> 3)) * 4, __float_as_uint(0.25f * rs));
      }
      bar_sync(1, 128);
      if (tid == 0) mbar_arrive(bar + 8 * B_ST);
      asm volatile("" : "+f"(rs), "+f"(mb)::"memory");
      tq0 = ldg128v(reinterpret_cast<const uint4*>(cT) + 5 * 128 + tid);
      tq1 = ldg128v(reinterpret_cast<const uint4*>(cT) + 6 * 128 + tid);
      const int R = 8 * (lane >> 4) + 2 * w + ((lane >> 3) & 1);
      ln_scatter<0>(xw, rs, -mb * rs, (sb + O_DATA + R * 128) ^ ((R & 7) << 4), (lane & 7) * 16);
    }
    if (tid == 0) TS(17);
    bar_sync(1, 128);
    fence_async_smem();
    const bool spec = (tid < 4);
    {
      const h2 wr = tq0.x, wi = tq0.y;
      const uint32_t cidx[5] = {tq0.z, tq0.w, tq1.x, tq1.y, tq1.z};
      h2 d[40];
      const uint32_t a = dlo(sb + O_CONST, 16), b = dlo(sb + O_DATA, 16);
      wg_fence();
#pragma unroll
      for (int k = 0; k < 4; k++) mma_h160k(d, a + 2 * k, HI_128, b + 2 * k, HI_128, k);
      wg_commit();
      wg_wait<0>();
      pin(d);
      if (tid == 0) TS(15);
      h2 pr[2][5], pi[2][5], qr[2][5], qi_[2][5];
#pragma unroll
      for (int sh = 0; sh < 2; sh++) {
#pragma unroll
        for (int a5 = 0; a5 < 5; a5++) {
          const h2 ar = d[8 * a5 + 2 * sh], ai = d[8 * a5 + 2 * sh + 1], br = d[8 * a5 + 4 + 2 * sh], bi = d[8 * a5 + 4 + 2 * sh + 1];
          pr[sh][a5] = hfnma(wi, bi, hfma(wr, br, ar));
          pi[sh][a5] = hfma(wi, br, hfma(wr, bi, ai));
          qr[sh][a5] = hfms(ar, H_TWO, pr[sh][a5]);
          qi_[sh][a5] = hfms(ai, H_TWO, pi[sh][a5]);
          if (spec) { pi[sh][a5] = qr[sh][a5]; qr[sh][a5] = ai; qi_[sh][a5] = hneg(bi); }
        }
        dft5(pr[sh], pi[sh]);
        dft5(qr[sh], qi_[sh]);
        if (spec) {
          const h2 r1 = pr[sh][1], i1 = pi[sh][1], r4 = pr[sh][4], i4 = pi[sh][4], r2 = pr[sh][2], i2 = pi[sh][2], r3 = pr[sh][3], i3 = pi[sh][3];
          pr[sh][1] = hmul(hadd(r1, r4), H_HALF); pi[sh][1] = hmul(hsub(i1, i4), H_HALF);
          pr[sh][4] = hmul(hadd(i1, i4), H_HALF); pi[sh][4] = hmul(hsub(r1, r4), H_HALF);
          pr[sh][2] = hmul(hadd(r2, r3), H_HALF); pi[sh][2] = hmul(hsub(i3, i2), H_HALF);
          pr[sh][3] = hmul(hadd(i2, i3), H_HALF); pi[sh][3] = hmul(hsub(r3, r2), H_HALF);
        }
      }
      bar_sync(1, 128);
      const uint32_t yb = (sb + O_DATA + t * 8) ^ ((slab & 24) << 1), b0 = ~(~t & 1);
#pragma unroll
      for (int j = 0; j < 5; j++) {
        const uint32_t y0 = (yb + (cidx[j] & 0x7fffu) * 64) ^ ((cidx[j] & 6) << 3), y1 = (yb + ((cidx[j] >> 16) & 0x7fffu) * 64) ^ ((cidx[j] >> 13) & 48);
        const uint32_t m0 = (cidx[j] & 0x8000u) ? 0x80008000u : 0u, m1 = (cidx[j] & 0x80000000u) ? 0x80008000u : 0u;
        sts64(y0, pr[0][j] & b0, pr[1][j]);
        if (j == 0 && spec) {
          sts64(yb + 320 * 64, pi[0][0] & b0, pi[1][0]);
          sts64(yb ^ 32, 0, 0);
          sts64((yb + 320 * 64) ^ 32, 0, 0);
        } else {
          sts64(y0 ^ 32, (pi[0][j] ^ m0) & b0, pi[1][j] ^ m0);
        }
        sts64(y1, qr[0][j] & b0, qr[1][j]);
        sts64(y1 ^ 32, (qi_[0][j] ^ m1) & b0, qi_[1][j] ^ m1);
      }
    }
    __syncwarp();
    if (lane == 0) mbar_arrive(bar + 8 * B_YS);
    if (tid == 0) TS(19);
    filter_convert<4>(sb, w, lane, 1 PROFARG);
    ColTw T;
    column_tw(T, cT, tid);
    h2 fac[4];
    const int nc = bid < 65 ? 3 : 2;
#pragma unroll 1
    for (int c = 0; c < nc; c++) {
      if (c < 2) {
        mbar_wait_lazy(bar + 8 * B_TD, c);
        mbar_wait_lazy(bar + 8 * (B_COL0 + c), 0);
      }
      if (tid == 0) TS2(47 + 2 * c);
      if (c == 0)
  {
      const uint2 own = lds64(sb + O_EB + (w * 4 + t) * 8);
      const uint32_t em = eb_max(sb, lane);
#pragma unroll
      for (int i = 0; i < 4; i++) {
        const uint32_t e2 = (i & 2 ? own.y : own.x) >> (16 * (i & 1));
        fac[i] = pack_h(__uint_as_float((127u - min(em - (e2 & 0xffu), 126u)) << 23), __uint_as_float((127u - min(em - ((e2 >> 8) & 0xffu), 126u)) << 23));
      }
    }
      column_one(sb, tid, sb + (c == 0 ? col_y(0) : c == 1 ? col_y(1) : col_y(2)), sb + (c == 0 ? col_w(0) : c == 1 ? col_w(1) : col_w(2)), T, fac);
      __syncwarp();
      if (lane == 0) mbar_arrive(bar + 8 * (B_ZD + c));
      if (tid == 0) TS2(48 + 2 * c);
    }
    if (tid == 0) TS(22);
  } else {
    asm volatile("setmaxnreg.inc.sync.aligned.u32 %0;" ::"n"(R_CONS));
    const int v = wgi & 1, w = tid >> 5, g = (tid & 31) >> 2;
    const int row = v * 64 + w * 16 + g;
    asm volatile("barrier.cluster.wait.acquire.aligned;" ::: "memory");
    const uint4 tq0 = ldg128v(reinterpret_cast<const uint4*>(cT) + 5 * 128 + tid);
    const uint4 tq1 = ldg128v(reinterpret_cast<const uint4*>(cT) + 6 * 128 + tid);
    Ring r{sb, bar, 0};
    float rh0 = 1.f, rh1 = 1.f;
    uint32_t m0 = 0, m1 = 0;
    {
      mbar_wait(bar + 8 * B_EPOCH, 0);
      const uint32_t ep = lds32(sb + O_EPOCH) + 1;
      const uint2* sp = g_stats + rb * 128 + row;
      uint2 q0, q1;
      int it = 0;
      mbar_wait(bar + 8 * B_ST, 0);
#pragma unroll 1
      do { q0 = ld_b64(sp); q1 = ld_b64(sp + 8); } while ((((q0.x ^ ep) | (q1.x ^ ep)) & 0xffff) && ++it < SPIN_MAX);
      m0 = __byte_perm(q0.x, 0, 0x3232); m1 = __byte_perm(q1.x, 0, 0x3232);
      rh0 = 0.5f * __uint_as_float(q0.y); rh1 = 0.5f * __uint_as_float(q1.y);
      __syncwarp();
    }
    if (tid == 0) TS(32 + 8 * v);
    {
      float ag[56], au[56];
#pragma unroll 1
      for (int tile = 0; tile < 2; tile++) {
        if (tile == 0) gemm1_tile<112>(ag, au, r, sb, v, tid, m0, m1 PROFARG); else gemm1_tile<104>(ag, au, r, sb, v, tid, m0, m1 PROFARG);
        pin(ag); pin(au);
        if (tid == 0) mbar_arrive(bar + 8 * B_TD);
        if (tid == 0) TS(32 + 8 * v + 1 + 2 * tile);
        if (tile) {
          mbar_wait(bar + 8 * (B_EMPTY + 6), 0);
        }
        mbar_wait(bar + 8 * (tile ? B_Z0F : B_DF), 0);
        const uint32_t hs = sb + (tile ? O_H2 + v * 13312 : O_CONST + v * 14336) + ((tid >> 4) & 1) * 1024 + (w * 16 + (tid & 15)) * 16;
#pragma unroll
        for (int i = 0; i < 6; i++) {
          uint32_t a0, a1, b0, b1;
          glu_group(ag + 8 * i, au + 8 * i, rh0, rh1, a0, a1);
          glu_group(ag + 8 * i + 4, au + 8 * i + 4, rh0, rh1, b0, b1);
          stsm4(hs + i * 2048, a0, a1, b0, b1);
        }
        uint32_t a0, a1;
        glu_group(ag + 48, au + 48, rh0, rh1, a0, a1);
        if (tile) {
          asm volatile("stmatrix.sync.aligned.m8n8.x2.shared.b16 [%0], {%1, %2};" ::"r"(hs + 6 * 2048), "r"(a0), "r"(a1) : "memory");
        } else {
          uint32_t b0, b1;
          glu_group(ag + 52, au + 52, rh0, rh1, b0, b1);
          stsm4(hs + 6 * 2048, a0, a1, b0, b1);
        }
        __syncwarp();
        if ((tid & 31) == 0) mbar_arrive(bar + 8 * B_HD);
        if (tid == 0) TS(32 + 8 * v + 2 + 2 * tile);
      }
    }
    {
      const int lane = tid & 31;
      {
        float acc[80];
        const uint32_t a = dlo(sb + v * 4096, 1024), b = dlo(sb + 8192, 1024);
#pragma unroll 1
        for (int lap = 0; lap < 3; lap++) {
#pragma unroll
          for (int i = 0; i < 9; i++) {
            mbar_wait(bar + 8 * (B_G2 + i), lap & 1);
            if (tid == 0 && v == 0) TS2(20 + lap * 9 + i);
            wg_fence();
            mma_b160(acc, a + i * (STG2_B >> 4), HI_0A, b + i * (STG2_B >> 4), HI_64, i ? 1 : lap);
            mma_b160(acc, a + i * (STG2_B >> 4) + 128, HI_0A, b + i * (STG2_B >> 4) + 320, HI_64, 1);
            wg_commit();
            wg_wait<1>();
            if (i ? lap < 2 : lap > 0) ring_release(bar + 8 * (B_G2 + (i + 8) % 9), tid);
          }
        }
        wg_wait<0>();
        pin(acc);
        if (tid == 0) TS(32 + 8 * v + 5);
        bar_sync(6, 256);
        const uint32_t ms = sb + O_MSG + (v * 4 + w) * 5120;
#pragma unroll
        for (int i = 0; i < 10; i++)
          sts128(ms + i * 512 + lane * 16, make_uint4(pack_bf(acc[8 * i], acc[8 * i + 1]) | 1, pack_bf(acc[8 * i + 2], acc[8 * i + 3]),
                                                      pack_bf(acc[8 * i + 4], acc[8 * i + 5]), pack_bf(acc[8 * i + 6], acc[8 * i + 7])));
        mbar_wait(bar + 8 * B_ZIN, 0);
        __syncwarp();
        if (elect()) {
          fence_async_smem();
          bulk_s2g(g_Y + (size_t)((rb * 8 + v * 4 + w) * 8 + slot) * 5120, ms, 5120);
          bulk_commit();
        }
      }
      if (tid == 0) TS(48 + 4 * v);
      inverse_rows(sb, tid, v, slab, tq0, tq1);
      bar_sync(6, 256);
      if (tid == 0) TS(v ? 28 : 18);
      mbar_wait(bar + 8 * B_X, 0);
      const uint32_t xt = sb + O_TEMP + (2 * w + v) * 2560, xa = xt + (lane & 15) * 160 + (lane >> 4) * 16;
      const uint32_t sa = sb + O_S + (2 * w + v) * 2560 + ((lane & 7) + (lane >> 4) * 8) * 32 + (((lane & 8) * 2) ^ ((lane & 4) << 2));
      const float rq0 = __uint_as_float(lds32(sb + O_RQ + g * 4)), rq1 = __uint_as_float(lds32(sb + O_RQ + g * 4 + 32));
      uint32_t xw[20], sw[20];
#pragma unroll
      for (int i = 0; i < 5; i++) {
        ldsm4(xa + i * 32, xw[4 * i], xw[4 * i + 1], xw[4 * i + 2], xw[4 * i + 3]);
        ldsm4t(sa + i * 512, sw[4 * i], sw[4 * i + 1], sw[4 * i + 2], sw[4 * i + 3]);
      }
      uint4 q[10];
      {
        const uint4* src = reinterpret_cast<const uint4*>(g_Y) + (slab * 8 + w) * 320 + v * 160 + lane;
        int it = 0;
        uint32_t ok;
#pragma unroll 1
        do {
          ok = 1;
#pragma unroll
          for (int i = 0; i < 10; i++) { q[i] = ld_b128(src + (i < 5 ? i * 32 : 4 * 320 + (i - 5) * 32)); ok &= q[i].x; }
        } while (!ok && ++it < SPIN_MAX);
      }
      if (tid == 0) TS(48 + 4 * v + 1);
#pragma unroll
      for (int i = 0; i < 5; i++) {
        const uint32_t pa[4] = {q[i].x, q[i].y, q[i].z, q[i].w}, pb[4] = {q[5 + i].x, q[5 + i].y, q[5 + i].z, q[5 + i].w};
#pragma unroll
        for (int j = 0; j < 4; j++) {
          const float rq = (j & 1) ? rq1 : rq0;
          const float d0 = (bf_lo(pa[j]) + bf_lo(pb[j])) * rq, d1 = (bf_hi(pa[j]) + bf_hi(pb[j])) * rq;
          const float g0 = fmaf(tanh_fast(d0), d0, d0), g1 = fmaf(tanh_fast(d1), d1, d1);
          xw[4 * i + j] = pack_bf(fmaf(bf_lo(sw[4 * i + j]), g0, bf_lo(xw[4 * i + j])), fmaf(bf_hi(sw[4 * i + j]), g1, bf_hi(xw[4 * i + j])));
        }
      }
#pragma unroll
      for (int i = 0; i < 5; i++) stsm4(xa + i * 32, xw[4 * i], xw[4 * i + 1], xw[4 * i + 2], xw[4 * i + 3]);
      __syncwarp();
      if (elect()) {
        fence_async_smem();
        tma2_st(&mp.out, 160 * w + 80 * v, slab * 16, xt);
        bulk_commit();
        asm volatile("cp.async.bulk.wait_group.read 0;" ::: "memory");
      }
      if (tid == 0) TS(32 + 8 * v + 6);
    }
  }
}

typedef CUresult (*EncodeFn)(CUtensorMap*, CUtensorMapDataType, cuuint32_t, void*, const cuuint64_t*, const cuuint64_t*, const cuuint32_t*,
                             const cuuint32_t*, CUtensorMapInterleave, CUtensorMapSwizzle, CUtensorMapL2promotion, CUtensorMapFloatOOBfill);

void encode(EncodeFn fn, CUtensorMap* m, const void* base, int rank, const cuuint64_t* dims, const cuuint64_t* strides, const cuuint32_t* box,
            CUtensorMapSwizzle swz, CUtensorMapDataType ty = CU_TENSOR_MAP_DATA_TYPE_BFLOAT16) {
  const cuuint32_t es[5] = {1, 1, 1, 1, 1};
  fn(m, ty, rank, const_cast<void*>(base), dims, strides, box, es, CU_TENSOR_MAP_INTERLEAVE_NONE, swz,
     CU_TENSOR_MAP_L2_PROMOTION_L2_128B, CU_TENSOR_MAP_FLOAT_OOB_FILL_NONE);
}

}

extern "C" void kernel_launch(void* const* d_in, const int* in_sizes, int n_in, void* d_out, int out_size) {
  (void)in_sizes; (void)n_in; (void)out_size;
  Params p;
  p.x = (const __nv_bfloat16*)d_in[0]; p.wr = (const __nv_bfloat16*)d_in[1]; p.wi = (const __nv_bfloat16*)d_in[2];
  p.wg = (const __nv_bfloat16*)d_in[4]; p.wu = (const __nv_bfloat16*)d_in[5]; p.wd = (const __nv_bfloat16*)d_in[6];
  p.out = (__nv_bfloat16*)d_out;
  static EncodeFn fn = nullptr;
  static void *scr = nullptr, *tab = nullptr;
  if (!fn) {
    void* f = nullptr;
    cudaDriverEntryPointQueryResult q;
    cudaGetDriverEntryPoint("cuTensorMapEncodeTiled", &f, cudaEnableDefault, &q);
    fn = (EncodeFn)f;
    cudaGetSymbolAddress(&scr, g_scr);
    cudaGetSymbolAddress(&tab, g_tab);
    cudaFuncSetAttribute(fused_kernel, cudaFuncAttributeMaxDynamicSharedMemorySize, SMEM_BYTES);
  }
  p.scr = (uint8_t*)scr; p.tab = (const uint32_t*)tab;
  uint8_t *yaddr = p.scr + G_Y, *zaddr = p.scr + G_Z;
  Maps mp;
  {
    const cuuint64_t d[2] = {640, 2048}, s[1] = {1280};
    const cuuint32_t b[2] = {64, 64};
    encode(fn, &mp.x, p.x, 2, d, s, b, CU_TENSOR_MAP_SWIZZLE_128B);
  }
  {
    const cuuint64_t d[2] = {1728, 640}, s[1] = {3456};
    for (int i = 0; i < 3; i++) {
      const cuuint32_t b[2] = {i == 0 ? 64u : i == 1 ? 48u : 40u, 32};
      encode(fn, &mp.w[0][i], p.wg, 2, d, s, b, CU_TENSOR_MAP_SWIZZLE_128B);
      encode(fn, &mp.w[1][i], p.wu, 2, d, s, b, CU_TENSOR_MAP_SWIZZLE_128B);
    }
  }
  {
    const cuuint64_t d[2] = {4096, 321}, s[1] = {8192};
    const cuuint32_t b[2] = {32, 56};
    encode(fn, &mp.ys[0], yaddr, 2, d, s, b, CU_TENSOR_MAP_SWIZZLE_64B);
    encode(fn, &mp.z, zaddr, 2, d, s, b, CU_TENSOR_MAP_SWIZZLE_64B);
    encode(fn, &mp.ys[1], (uint8_t*)yaddr + 321 * 8192, 2, d, s, b, CU_TENSOR_MAP_SWIZZLE_64B);
  }
  {
    const cuuint64_t d[2] = {640, 2048}, s[1] = {1280};
    const cuuint32_t b2[2] = {80, 16};
    encode(fn, &mp.xf, p.x, 2, d, s, b2, CU_TENSOR_MAP_SWIZZLE_NONE);
    encode(fn, &mp.out, p.out, 2, d, s, b2, CU_TENSOR_MAP_SWIZZLE_NONE);
  }
  {
    const cuuint64_t d[3] = {164, 8, 256}, s[2] = {640, 5136};
    const cuuint32_t b[3] = {164, 8, 1};
    encode(fn, &mp.wf[0], p.wr, 3, d, s, b, CU_TENSOR_MAP_SWIZZLE_NONE, CU_TENSOR_MAP_DATA_TYPE_UINT32);
    encode(fn, &mp.wf[1], p.wi, 3, d, s, b, CU_TENSOR_MAP_SWIZZLE_NONE, CU_TENSOR_MAP_DATA_TYPE_UINT32);
  }
  {
    const cuuint64_t d[3] = {32, 1728, 20}, s[2] = {1280, 64};
    const cuuint32_t b[3] = {32, 16, 5};
    encode(fn, &mp.wd, p.wd, 3, d, s, b, CU_TENSOR_MAP_SWIZZLE_64B);
  }
  fused_kernel<<<128, 512, SMEM_BYTES>>>(p, mp);
}
```
